```python
import torch

def _softmax(x, axis=-1):
    return torch.softmax(x, dim=axis)
def _gelu(x):
    return torch.nn.functional.gelu(x, approximate="tanh")
def _silu(x):
    return torch.nn.functional.silu(x)
def _sigmoid(x):
    return torch.sigmoid(x)
def _layernorm(x, axis=-1, eps=1e-5):
    m = x.mean(dim=axis, keepdim=True)
    v = x.var(dim=axis, keepdim=True, unbiased=False)
    return (x - m) / torch.sqrt(v + eps)
def _scatter_add(tgt, idx, src, axis=0):
    return tgt.clone().index_add_(axis, idx, src)
def _segment_sum(src, seg, n):
    out = torch.zeros((n,) + src.shape[1:], dtype=src.dtype)
    return out.index_add_(0, seg, src)
def _pad(x, pw):
    flat = tuple(v for pair in reversed(pw) for v in pair)
    return torch.nn.functional.pad(x, flat)

kernel_name = 'concat_heads__mha_block_cached__gqa_block_cached__near_ridge'

def setup_inputs():

    _w = (lambda a: (lambda t: t.to(torch.bfloat16) if t.is_floating_point() else t)(torch.as_tensor(a)))
    def _A_setup():
        B, Sq, D = 8, 128, 512
        H, Sk, Dh = 32, 128, 128
        return {
            "x": _w((lambda *s: torch.randn(*s, dtype=torch.bfloat16) * 0.8)(B, Sq, D)),
            "k_cache": _w((lambda *s: torch.randn(*s, dtype=torch.bfloat16) * 0.8)(B, H, Sk, Dh)),
            "v_cache": _w((lambda *s: torch.randn(*s, dtype=torch.bfloat16) * 0.05)(B, H, Sk, Dh)),
            "wq": _w((lambda *s: torch.randn(*s, dtype=torch.bfloat16) * 0.8)(D, H * Dh) * (D ** -0.5)),
            "wo": _w((lambda *s: torch.randn(*s, dtype=torch.bfloat16) * 0.05)(H * Dh, D) * ((H * Dh) ** -0.5)),
        }
    _A_in = _A_setup()

    def _B_setup():
        B, Sq, D = 8, 128, 512
        Hq, Hkv, Sk, Dh = 32, 32, 128, 128
        assert Hq % Hkv == 0, (Hq, Hkv)
        return {
            "x": _w((lambda *s: torch.randn(*s, dtype=torch.bfloat16) * 0.8)(B, Sq, D)),
            "k_cache": _w((lambda *s: torch.randn(*s, dtype=torch.bfloat16) * 0.8)(B, Hkv, Sk, Dh)),
            "v_cache": _w((lambda *s: torch.randn(*s, dtype=torch.bfloat16) * 0.05)(B, Hkv, Sk, Dh)),
            "wq": _w((lambda *s: torch.randn(*s, dtype=torch.bfloat16) * 0.8)(D, Hq * Dh) * (D ** -0.5)),
            "wo": _w((lambda *s: torch.randn(*s, dtype=torch.bfloat16) * 0.05)(Hq * Dh, D) * ((Hq * Dh) ** -0.5)),
        }
    _B_in = _B_setup()

    return {
        "A_x": _A_in["x"],
        "A_k_cache": _A_in["k_cache"],
        "A_v_cache": _A_in["v_cache"],
        "A_wq": _A_in["wq"],
        "A_wo": _A_in["wo"],
        "B_x": _B_in["x"],
        "B_k_cache": _B_in["k_cache"],
        "B_v_cache": _B_in["v_cache"],
        "B_wq": _B_in["wq"],
        "B_wo": _B_in["wo"],
    }

def reference(A_x, A_k_cache, A_v_cache, A_wq, A_wo, B_x, B_k_cache, B_v_cache, B_wq, B_wo):
    def _A_ref(x, k_cache, v_cache, wq, wo):
        B, Sq, D = x.shape
        H, Dh = 32, 128
        q = (lambda x, *d: x.permute(*d))((x @ wq).reshape(B, Sq, H, Dh), 0, 2, 1, 3)
        scores = torch.einsum("bhqd,bhkd->bhqk", q, k_cache) * (Dh ** -0.5)
        p = _softmax(scores, axis=-1)
        o = torch.einsum("bhqk,bhkd->bhqd", p, v_cache)
        return (lambda x, *d: x.permute(*d))(o, 0, 2, 1, 3).reshape(B, Sq, H * Dh) @ wo

    def _B_ref(x, k_cache, v_cache, wq, wo):
        B, Sq, D = x.shape
        Hq, Dh = 32, 128
        Hkv = k_cache.shape[1]
        rep = Hq // Hkv
        q = (lambda x, *d: x.permute(*d))((x @ wq).reshape(B, Sq, Hq, Dh), 0, 2, 1, 3)
        k = (lambda x, n, axis: torch.repeat_interleave(x, n, dim=axis))(k_cache, rep, axis=1)
        v = (lambda x, n, axis: torch.repeat_interleave(x, n, dim=axis))(v_cache, rep, axis=1)
        scores = torch.einsum("bhqd,bhkd->bhqk", q, k) * (Dh ** -0.5)
        p = _softmax(scores, axis=-1)
        o = torch.einsum("bhqk,bhkd->bhqd", p, v)
        return (lambda x, *d: x.permute(*d))(o, 0, 2, 1, 3).reshape(B, Sq, Hq * Dh) @ wo

    a = _A_ref(A_x, A_k_cache, A_v_cache, A_wq, A_wo)
    b = _B_ref(B_x, B_k_cache, B_v_cache, B_wq, B_wo)
    return torch.concatenate([a, b], axis=-1)
```

```cpp
#include <cuda_runtime.h>
#include <cuda_bf16.h>
#include <cuda.h>
#include <stdint.h>

namespace {

constexpr int SLOT = 32768;
constexpr int NSLOT = 7;
constexpr int SMEM_BYTES = NSLOT * SLOT + 1024   + 1024  ;
constexpr int FT = 0;
constexpr int FX = 40;
constexpr int ET = 48;
constexpr int SF = 84;
constexpr int SE = 94;
constexpr int RG = 102;
constexpr int NBAR = 112;
constexpr int NFLUSH = 5;
__host__ __device__ constexpr int ttype(int t) {
  return t < 8 ? 4 : (t == 8 || t == 15 || t == 20 || t == 24) ? 0 : (t == 12 || t == 19 || t == 23 || t == 28) ? 1 : (t < 19 ? 2 : 3);
}
__host__ __device__ constexpr uint64_t types_8_39() {
  uint64_t r = 0;
  for (int t = 8; t < 40; t++) r |= (uint64_t)ttype(t) << (2 * (t - 8));
  return r;
}
__host__ __device__ constexpr int tslot(int t) { return t < 20 ? 4 + t % 3 : (0x5462 >> (4 * (t & 3))) & 0xF; }
__host__ __device__ constexpr int tpred(int t) { return t < 21 ? t - 3 : t - 4; }
__host__ __device__ constexpr uint32_t local_only() {
  uint32_t r = 0xFFFFFFFFu;
  for (int t = 3; t < 36; t++)
    if (ttype(t) >= 2) r &= ~(1u << tpred(t));
  return r;
}
constexpr uint32_t LOCAL_ONLY = local_only();
constexpr uint64_t ULIST = 0xFED32CBA98765410ull;

struct Params {
  CUtensorMap x[2], wq[2], wq2[2], k[2], v[2], wo[2], out;
  const char* x_ptr[2];
  const char* wq_ptr[2];
  const char* k_ptr[2];
  const char* v_ptr[2];
  const char* wo_ptr[2];
  char* out_ptr;
  uint32_t zero;
};

__device__ unsigned int g_zero_cnt[16 * 32];
#define PROF(idx) do {} while (0)
#define PROFW(idx) do {} while (0)
#define FINE(blk, ev) do {} while (0)

__device__ __forceinline__ uint32_t smem_u32(const void* p) { return (uint32_t)__cvta_generic_to_shared(p); }
__device__ __forceinline__ bool elect_one() {
  uint32_t r;
  asm volatile("{\n.reg .pred p;\nelect.sync _|p, 0xffffffff;\nselp.u32 %0, 1, 0, p;\n}" : "=r"(r));
  return r;
}
__device__ __forceinline__ void mbar_init(uint32_t bar, uint32_t cnt) {
  asm volatile("mbarrier.init.shared::cta.b64 [%0], %1;" ::"r"(bar), "r"(cnt) : "memory");
}
__device__ __forceinline__ void mbar_expect_tx(uint32_t bar, uint32_t bytes) {
  asm volatile("mbarrier.arrive.expect_tx.shared::cta.b64 _, [%0], %1;" ::"r"(bar), "r"(bytes) : "memory");
}
__device__ __forceinline__ void mbar_arrive(uint32_t bar) {
  asm volatile("mbarrier.arrive.shared::cta.b64 _, [%0];" ::"r"(bar) : "memory");
}
__device__ __forceinline__ void mbar_arrive_cluster(uint32_t bar_cluster_addr) {
  asm volatile("mbarrier.arrive.shared::cluster.b64 _, [%0];" ::"r"(bar_cluster_addr) : "memory");
}
__device__ __forceinline__ bool mbar_try(uint32_t bar) {
  uint32_t ok;
  asm volatile("{\n.reg .pred p;\nmbarrier.try_wait.parity.shared::cta.b64 p, [%1], 0;\nselp.u32 %0, 1, 0, p;\n}"
               : "=r"(ok) : "r"(bar) : "memory");
  return ok;
}
__device__ __forceinline__ void mbar_wait(uint32_t bar) {
  if (mbar_try(bar)) return;
#pragma unroll 1
  for (int i = 0; i < (1 << 24); i++)
    if (mbar_try(bar)) return;
  __trap();
}
__device__ __forceinline__ void tma_2d(uint32_t dst, const CUtensorMap* tm, int c0, int c1, uint32_t bar) {
  asm volatile("cp.async.bulk.tensor.2d.shared::cluster.global.mbarrier::complete_tx::bytes [%0], [%1, {%3, %4}], [%2];"
               ::"r"(dst), "l"(tm), "r"(bar), "r"(c0), "r"(c1) : "memory");
}
__device__ __forceinline__ void tma_3d(uint32_t dst, const CUtensorMap* tm, int c0, int c1, int c2, uint32_t bar) {
  asm volatile("cp.async.bulk.tensor.3d.shared::cluster.global.mbarrier::complete_tx::bytes [%0], [%1, {%3, %4, %5}], [%2];"
               ::"r"(dst), "l"(tm), "r"(bar), "r"(c0), "r"(c1), "r"(c2) : "memory");
}
__device__ __forceinline__ void tma_3d_hint(uint32_t dst, const CUtensorMap* tm, int c0, int c1, int c2, uint32_t bar, uint64_t pol) {
  asm volatile("cp.async.bulk.tensor.3d.shared::cluster.global.mbarrier::complete_tx::bytes.L2::cache_hint [%0], [%1, {%3, %4, %5}], [%2], %6;"
               ::"r"(dst), "l"(tm), "r"(bar), "r"(c0), "r"(c1), "r"(c2), "l"(pol) : "memory");
}
__device__ __forceinline__ void tma_2d_mc(uint32_t dst, const CUtensorMap* tm, int c0, int c1, uint32_t bar) {
  asm volatile("cp.async.bulk.tensor.2d.shared::cluster.global.mbarrier::complete_tx::bytes.multicast::cluster [%0], [%1, {%3, %4}], [%2], %5;"
               ::"r"(dst), "l"(tm), "r"(bar), "r"(c0), "r"(c1), "h"((uint16_t)3) : "memory");
}
__device__ __forceinline__ void tma_3d_mc(uint32_t dst, const CUtensorMap* tm, int c0, int c1, int c2, uint32_t bar) {
  asm volatile("cp.async.bulk.tensor.3d.shared::cluster.global.mbarrier::complete_tx::bytes.multicast::cluster [%0], [%1, {%3, %4, %5}], [%2], %6;"
               ::"r"(dst), "l"(tm), "r"(bar), "r"(c0), "r"(c1), "r"(c2), "h"((uint16_t)3) : "memory");
}
__device__ __forceinline__ uint64_t mkdesc(uint32_t addr, uint32_t lbo, uint32_t sbo) {
  return (uint64_t)((addr & 0x3FFFF) >> 4) | ((uint64_t)(lbo >> 4) << 16) | ((uint64_t)(sbo >> 4) << 32) | (1ULL << 62);
}
__device__ __forceinline__ uint32_t pack_bf16(float lo, float hi) {
  uint32_t r;
  asm("cvt.rn.bf16x2.f32 %0, %1, %2;" : "=r"(r) : "f"(hi), "f"(lo));
  return r;
}
__device__ __forceinline__ float ex2(float x) {
  float r;
  asm("ex2.approx.ftz.f32 %0, %1;" : "=f"(r) : "f"(x));
  return r;
}
#define SCHED_FENCE() mbar_wait(c.bars + FX * 8)
#define WG_FENCE() asm volatile("wgmma.fence.sync.aligned;" ::: "memory")
#define WG_COMMIT() asm volatile("wgmma.commit_group.sync.aligned;" ::: "memory")
#define WG_WAIT(n) asm volatile("wgmma.wait_group.sync.aligned %0;" ::"n"(n) : "memory")
template <int N>
__device__ __forceinline__ void fence_acc(float (&d)[N]) {
#pragma unroll
  for (int i = 0; i < N; i++) asm volatile("" : "+f"(d[i])::"memory");
}
template <int N, int OFF, int TOT>
__device__ __forceinline__ void fence_frag(uint32_t (&d)[TOT]) {
#pragma unroll
  for (int i = 0; i < N; i++) asm volatile("" : "+r"(d[OFF + i])::"memory");
}

__device__ __forceinline__ void wgmma_ss_n256_tb1(float (&d)[128], uint64_t da, uint64_t db, int scale_d) {
  asm volatile("{\n.reg .pred p;\nsetp.ne.b32 p, %130, 0;\n"
      "wgmma.mma_async.sync.aligned.m64n256k16.f32.bf16.bf16 {"
      "%0, %1, %2, %3, %4, %5, %6, %7, %8, %9, %10, %11, %12, %13, %14, %15, %16, %17, %18, %19, %20, %21, %22, %23, %24, %25, %26, %27, %28, %29, %30, %31, "
      "%32, %33, %34, %35, %36, %37, %38, %39, %40, %41, %42, %43, %44, %45, %46, %47, %48, %49, %50, %51, %52, %53, %54, %55, %56, %57, %58, %59, %60, %61, %62, %63, "
      "%64, %65, %66, %67, %68, %69, %70, %71, %72, %73, %74, %75, %76, %77, %78, %79, %80, %81, %82, %83, %84, %85, %86, %87, %88, %89, %90, %91, %92, %93, %94, %95, "
      "%96, %97, %98, %99, %100, %101, %102, %103, %104, %105, %106, %107, %108, %109, %110, %111, %112, %113, %114, %115, %116, %117, %118, %119, %120, %121, %122, %123, %124, %125, %126, %127"
      "}, %128, %129, p, 1, 1, 0, 1;\n}\n"
    :
      "+f"(d[0]), "+f"(d[1]), "+f"(d[2]), "+f"(d[3]), "+f"(d[4]), "+f"(d[5]), "+f"(d[6]), "+f"(d[7]),
      "+f"(d[8]), "+f"(d[9]), "+f"(d[10]), "+f"(d[11]), "+f"(d[12]), "+f"(d[13]), "+f"(d[14]), "+f"(d[15]),
      "+f"(d[16]), "+f"(d[17]), "+f"(d[18]), "+f"(d[19]), "+f"(d[20]), "+f"(d[21]), "+f"(d[22]), "+f"(d[23]),
      "+f"(d[24]), "+f"(d[25]), "+f"(d[26]), "+f"(d[27]), "+f"(d[28]), "+f"(d[29]), "+f"(d[30]), "+f"(d[31]),
      "+f"(d[32]), "+f"(d[33]), "+f"(d[34]), "+f"(d[35]), "+f"(d[36]), "+f"(d[37]), "+f"(d[38]), "+f"(d[39]),
      "+f"(d[40]), "+f"(d[41]), "+f"(d[42]), "+f"(d[43]), "+f"(d[44]), "+f"(d[45]), "+f"(d[46]), "+f"(d[47]),
      "+f"(d[48]), "+f"(d[49]), "+f"(d[50]), "+f"(d[51]), "+f"(d[52]), "+f"(d[53]), "+f"(d[54]), "+f"(d[55]),
      "+f"(d[56]), "+f"(d[57]), "+f"(d[58]), "+f"(d[59]), "+f"(d[60]), "+f"(d[61]), "+f"(d[62]), "+f"(d[63]),
      "+f"(d[64]), "+f"(d[65]), "+f"(d[66]), "+f"(d[67]), "+f"(d[68]), "+f"(d[69]), "+f"(d[70]), "+f"(d[71]),
      "+f"(d[72]), "+f"(d[73]), "+f"(d[74]), "+f"(d[75]), "+f"(d[76]), "+f"(d[77]), "+f"(d[78]), "+f"(d[79]),
      "+f"(d[80]), "+f"(d[81]), "+f"(d[82]), "+f"(d[83]), "+f"(d[84]), "+f"(d[85]), "+f"(d[86]), "+f"(d[87]),
      "+f"(d[88]), "+f"(d[89]), "+f"(d[90]), "+f"(d[91]), "+f"(d[92]), "+f"(d[93]), "+f"(d[94]), "+f"(d[95]),
      "+f"(d[96]), "+f"(d[97]), "+f"(d[98]), "+f"(d[99]), "+f"(d[100]), "+f"(d[101]), "+f"(d[102]), "+f"(d[103]),
      "+f"(d[104]), "+f"(d[105]), "+f"(d[106]), "+f"(d[107]), "+f"(d[108]), "+f"(d[109]), "+f"(d[110]), "+f"(d[111]),
      "+f"(d[112]), "+f"(d[113]), "+f"(d[114]), "+f"(d[115]), "+f"(d[116]), "+f"(d[117]), "+f"(d[118]), "+f"(d[119]),
      "+f"(d[120]), "+f"(d[121]), "+f"(d[122]), "+f"(d[123]), "+f"(d[124]), "+f"(d[125]), "+f"(d[126]), "+f"(d[127])
    : "l"(da), "l"(db), "r"(scale_d));
}
__device__ __forceinline__ void wgmma_ss_n128_tb1(float (&d)[64], uint64_t da, uint64_t db, int scale_d) {
  asm volatile("{\n.reg .pred p;\nsetp.ne.b32 p, %66, 0;\n"
      "wgmma.mma_async.sync.aligned.m64n128k16.f32.bf16.bf16 {"
      "%0, %1, %2, %3, %4, %5, %6, %7, %8, %9, %10, %11, %12, %13, %14, %15, %16, %17, %18, %19, %20, %21, %22, %23, %24, %25, %26, %27, %28, %29, %30, %31, "
      "%32, %33, %34, %35, %36, %37, %38, %39, %40, %41, %42, %43, %44, %45, %46, %47, %48, %49, %50, %51, %52, %53, %54, %55, %56, %57, %58, %59, %60, %61, %62, %63"
      "}, %64, %65, p, 1, 1, 0, 1;\n}\n"
    :
      "+f"(d[0]), "+f"(d[1]), "+f"(d[2]), "+f"(d[3]), "+f"(d[4]), "+f"(d[5]), "+f"(d[6]), "+f"(d[7]),
      "+f"(d[8]), "+f"(d[9]), "+f"(d[10]), "+f"(d[11]), "+f"(d[12]), "+f"(d[13]), "+f"(d[14]), "+f"(d[15]),
      "+f"(d[16]), "+f"(d[17]), "+f"(d[18]), "+f"(d[19]), "+f"(d[20]), "+f"(d[21]), "+f"(d[22]), "+f"(d[23]),
      "+f"(d[24]), "+f"(d[25]), "+f"(d[26]), "+f"(d[27]), "+f"(d[28]), "+f"(d[29]), "+f"(d[30]), "+f"(d[31]),
      "+f"(d[32]), "+f"(d[33]), "+f"(d[34]), "+f"(d[35]), "+f"(d[36]), "+f"(d[37]), "+f"(d[38]), "+f"(d[39]),
      "+f"(d[40]), "+f"(d[41]), "+f"(d[42]), "+f"(d[43]), "+f"(d[44]), "+f"(d[45]), "+f"(d[46]), "+f"(d[47]),
      "+f"(d[48]), "+f"(d[49]), "+f"(d[50]), "+f"(d[51]), "+f"(d[52]), "+f"(d[53]), "+f"(d[54]), "+f"(d[55]),
      "+f"(d[56]), "+f"(d[57]), "+f"(d[58]), "+f"(d[59]), "+f"(d[60]), "+f"(d[61]), "+f"(d[62]), "+f"(d[63])
    : "l"(da), "l"(db), "r"(scale_d));
}
__device__ __forceinline__ void wgmma_rs_n128_tb0(float (&d)[64], uint32_t a0, uint32_t a1, uint32_t a2, uint32_t a3, uint64_t db, int scale_d) {
  asm volatile("{\n.reg .pred p;\nsetp.ne.b32 p, %69, 0;\n"
      "wgmma.mma_async.sync.aligned.m64n128k16.f32.bf16.bf16 {"
      "%0, %1, %2, %3, %4, %5, %6, %7, %8, %9, %10, %11, %12, %13, %14, %15, %16, %17, %18, %19, %20, %21, %22, %23, %24, %25, %26, %27, %28, %29, %30, %31, "
      "%32, %33, %34, %35, %36, %37, %38, %39, %40, %41, %42, %43, %44, %45, %46, %47, %48, %49, %50, %51, %52, %53, %54, %55, %56, %57, %58, %59, %60, %61, %62, %63"
      "}, {%64, %65, %66, %67}, %68, p, 1, 1, 0;\n}\n"
    :
      "+f"(d[0]), "+f"(d[1]), "+f"(d[2]), "+f"(d[3]), "+f"(d[4]), "+f"(d[5]), "+f"(d[6]), "+f"(d[7]),
      "+f"(d[8]), "+f"(d[9]), "+f"(d[10]), "+f"(d[11]), "+f"(d[12]), "+f"(d[13]), "+f"(d[14]), "+f"(d[15]),
      "+f"(d[16]), "+f"(d[17]), "+f"(d[18]), "+f"(d[19]), "+f"(d[20]), "+f"(d[21]), "+f"(d[22]), "+f"(d[23]),
      "+f"(d[24]), "+f"(d[25]), "+f"(d[26]), "+f"(d[27]), "+f"(d[28]), "+f"(d[29]), "+f"(d[30]), "+f"(d[31]),
      "+f"(d[32]), "+f"(d[33]), "+f"(d[34]), "+f"(d[35]), "+f"(d[36]), "+f"(d[37]), "+f"(d[38]), "+f"(d[39]),
      "+f"(d[40]), "+f"(d[41]), "+f"(d[42]), "+f"(d[43]), "+f"(d[44]), "+f"(d[45]), "+f"(d[46]), "+f"(d[47]),
      "+f"(d[48]), "+f"(d[49]), "+f"(d[50]), "+f"(d[51]), "+f"(d[52]), "+f"(d[53]), "+f"(d[54]), "+f"(d[55]),
      "+f"(d[56]), "+f"(d[57]), "+f"(d[58]), "+f"(d[59]), "+f"(d[60]), "+f"(d[61]), "+f"(d[62]), "+f"(d[63])
    : "r"(a0), "r"(a1), "r"(a2), "r"(a3), "l"(db), "r"(scale_d));
}
__device__ __forceinline__ void wgmma_rs_n128_tb1(float (&d)[64], uint32_t a0, uint32_t a1, uint32_t a2, uint32_t a3, uint64_t db, int scale_d) {
  asm volatile("{\n.reg .pred p;\nsetp.ne.b32 p, %69, 0;\n"
      "wgmma.mma_async.sync.aligned.m64n128k16.f32.bf16.bf16 {"
      "%0, %1, %2, %3, %4, %5, %6, %7, %8, %9, %10, %11, %12, %13, %14, %15, %16, %17, %18, %19, %20, %21, %22, %23, %24, %25, %26, %27, %28, %29, %30, %31, "
      "%32, %33, %34, %35, %36, %37, %38, %39, %40, %41, %42, %43, %44, %45, %46, %47, %48, %49, %50, %51, %52, %53, %54, %55, %56, %57, %58, %59, %60, %61, %62, %63"
      "}, {%64, %65, %66, %67}, %68, p, 1, 1, 1;\n}\n"
    :
      "+f"(d[0]), "+f"(d[1]), "+f"(d[2]), "+f"(d[3]), "+f"(d[4]), "+f"(d[5]), "+f"(d[6]), "+f"(d[7]),
      "+f"(d[8]), "+f"(d[9]), "+f"(d[10]), "+f"(d[11]), "+f"(d[12]), "+f"(d[13]), "+f"(d[14]), "+f"(d[15]),
      "+f"(d[16]), "+f"(d[17]), "+f"(d[18]), "+f"(d[19]), "+f"(d[20]), "+f"(d[21]), "+f"(d[22]), "+f"(d[23]),
      "+f"(d[24]), "+f"(d[25]), "+f"(d[26]), "+f"(d[27]), "+f"(d[28]), "+f"(d[29]), "+f"(d[30]), "+f"(d[31]),
      "+f"(d[32]), "+f"(d[33]), "+f"(d[34]), "+f"(d[35]), "+f"(d[36]), "+f"(d[37]), "+f"(d[38]), "+f"(d[39]),
      "+f"(d[40]), "+f"(d[41]), "+f"(d[42]), "+f"(d[43]), "+f"(d[44]), "+f"(d[45]), "+f"(d[46]), "+f"(d[47]),
      "+f"(d[48]), "+f"(d[49]), "+f"(d[50]), "+f"(d[51]), "+f"(d[52]), "+f"(d[53]), "+f"(d[54]), "+f"(d[55]),
      "+f"(d[56]), "+f"(d[57]), "+f"(d[58]), "+f"(d[59]), "+f"(d[60]), "+f"(d[61]), "+f"(d[62]), "+f"(d[63])
    : "r"(a0), "r"(a1), "r"(a2), "r"(a3), "l"(db), "r"(scale_d));
}

__device__ __forceinline__ void turn_wait(int wg) { asm volatile("bar.sync %0, 256;" ::"r"(1 + wg) : "memory"); }
__device__ __forceinline__ void turn_pass(int wg) { asm volatile("bar.arrive %0, 256;" ::"r"(2 - wg) : "memory"); }

__device__ __forceinline__ void release(uint32_t rel_base, int idx, int nl) {
  if ((int)(threadIdx.x & 31) < nl) mbar_arrive_cluster(rel_base + idx * 8);
}

#define SEG2A 7
#define SEG3A 4
#define SEG3B 10
constexpr float SM_C = 0.08838834764831845f * 1.4426950408889634f;

__device__ __forceinline__ void issue_s(float (&sc)[64], uint32_t (&q)[32], uint32_t kaddr, int acc0) {
  const uint64_t dk = mkdesc(kaddr, 16, 1024);
#pragma unroll
  for (int j = 0; j < 8; j++)
    wgmma_rs_n128_tb0(sc, q[4 * j], q[4 * j + 1], q[4 * j + 2], q[4 * j + 3], dk + (j >> 2) * 1024 + (j & 3) * 2, j != 0 ? 1 : acc0);
}
__device__ __forceinline__ void issue_nt(float (&d)[64], uint32_t (&a)[32], uint32_t baddr, int acc0) {
  const uint64_t db = mkdesc(baddr, 16384, 1024);
#pragma unroll
  for (int j = 0; j < 8; j++)
    wgmma_rs_n128_tb1(d, a[4 * j], a[4 * j + 1], a[4 * j + 2], a[4 * j + 3], db + j * 128, j != 0 ? 1 : acc0);
}
__device__ __forceinline__ void issue_q(float (&d)[64], uint32_t xaddr, uint32_t baddr, int acc0) {
  asm volatile("" : "+r"(xaddr));
  const uint64_t da = mkdesc(xaddr, 16, 1024);
  const uint64_t db = mkdesc(baddr, 16384, 1024);
#pragma unroll
  for (int j = 0; j < 8; j++) wgmma_ss_n128_tb1(d, da + (j >> 2) * 1024 + (j & 3) * 2, db + j * 128, j != 0 ? 1 : acc0);
}
__device__ __forceinline__ void softmax_max(float (&sc)[64], float& n0, float& n1) {
  float a0[4], a1[4];
#pragma unroll
  for (int q = 0; q < 4; q++) {
    a0[q] = fmaxf(fmaxf(sc[16 * q], sc[16 * q + 1]), fmaxf(sc[16 * q + 4], sc[16 * q + 5]));
    a1[q] = fmaxf(fmaxf(sc[16 * q + 2], sc[16 * q + 3]), fmaxf(sc[16 * q + 6], sc[16 * q + 7]));
    a0[q] = fmaxf(a0[q], fmaxf(fmaxf(sc[16 * q + 8], sc[16 * q + 9]), fmaxf(sc[16 * q + 12], sc[16 * q + 13])));
    a1[q] = fmaxf(a1[q], fmaxf(fmaxf(sc[16 * q + 10], sc[16 * q + 11]), fmaxf(sc[16 * q + 14], sc[16 * q + 15])));
  }
  n0 = fmaxf(fmaxf(a0[0], a0[1]), fmaxf(a0[2], a0[3]));
  n1 = fmaxf(fmaxf(a1[0], a1[1]), fmaxf(a1[2], a1[3]));
  asm volatile("" : "+f"(n0), "+f"(n1)::"memory");
}
__device__ __forceinline__ void softmax_max_finish(float& n0, float& n1) {
  n0 = fmaxf(n0, __shfl_xor_sync(0xffffffffu, n0, 1));
  n1 = fmaxf(n1, __shfl_xor_sync(0xffffffffu, n1, 1));
  n0 = fmaxf(n0, __shfl_xor_sync(0xffffffffu, n0, 2));
  n1 = fmaxf(n1, __shfl_xor_sync(0xffffffffu, n1, 2));
  n0 *= -SM_C;
  n1 *= -SM_C;
}
template <int J0, int J1>
__device__ __forceinline__ void softmax_exp(float (&sc)[64], uint32_t (&pf)[32], float n0, float n1, float& l0, float& l1) {
#pragma unroll
  for (int j = J0; j < J1; j++) {
    const float e0 = ex2(fmaf(sc[4 * j], SM_C, n0));
    const float e1 = ex2(fmaf(sc[4 * j + 1], SM_C, n0));
    const float e2 = ex2(fmaf(sc[4 * j + 2], SM_C, n1));
    const float e3 = ex2(fmaf(sc[4 * j + 3], SM_C, n1));
    l0 += e0 + e1;
    l1 += e2 + e3;
    pf[2 * j] = pack_bf16(e0, e1);
    pf[2 * j + 1] = pack_bf16(e2, e3);
  }
  asm volatile("" : "+f"(l0), "+f"(l1)::"memory");
#pragma unroll
  for (int j = 2 * J0; j < 2 * J1; j++) asm volatile("" : "+r"(pf[j])::"memory");
}
__device__ __forceinline__ void row_inv(float& l0, float& l1) {
  l0 += __shfl_xor_sync(0xffffffffu, l0, 1);
  l1 += __shfl_xor_sync(0xffffffffu, l1, 1);
  l0 += __shfl_xor_sync(0xffffffffu, l0, 2);
  l1 += __shfl_xor_sync(0xffffffffu, l1, 2);
  l0 = __fdividef(1.f, l0);
  l1 = __fdividef(1.f, l1);
}
__device__ __forceinline__ void cvt_frag(uint32_t (&f)[32], float (&a)[64]) {
#pragma unroll
  for (int i = 0; i < 32; i++) f[i] = pack_bf16(a[2 * i], a[2 * i + 1]);
}

struct Ctx {
  uint32_t sb, bars, rel_base;
  int wg;
  int z;
};
template <int T>
__device__ __forceinline__ void blk_begin(const Ctx& c) {
  mbar_wait(c.bars + (FT + T) * 8);
  turn_wait(c.wg);
}
template <int T>
__device__ __forceinline__ void blk_release(const Ctx& c) {
  FINE(T, 4);
  if (T < 36) release(c.rel_base, ET + T, ((LOCAL_ONLY >> (T & 31)) & 1) && T < 32 ? 1 : 2);
}
template <int T>
__device__ __forceinline__ uint32_t tile_addr(const Ctx& c) {
  uint32_t a = c.sb;
  asm volatile("" : "+r"(a));
  return a + tslot(T) * SLOT;
}

__device__ __forceinline__ void stsm(uint32_t addr, uint32_t a, uint32_t b, uint32_t c, uint32_t d) {
  asm volatile("stmatrix.sync.aligned.m8n8.x4.shared.b16 [%0], {%1, %2, %3, %4};" ::"r"(addr), "r"(a), "r"(b), "r"(c), "r"(d) : "memory");
}
__device__ __forceinline__ uint32_t st_addr(uint32_t row, int sw, int e) { return row + (e >> 2) * 16384 + (((2 * (e & 3)) ^ sw) << 4); }
__device__ __forceinline__ void proxy_fence() { asm volatile("fence.proxy.async.shared::cta;" ::: "memory"); }
__device__ __forceinline__ void st_frag(uint32_t row, int sw, uint32_t (&f)[32]) {
#pragma unroll
  for (int e = 0; e < 8; e++) stsm(st_addr(row, sw, e), f[4 * e], f[4 * e + 1], f[4 * e + 2], f[4 * e + 3]);
}
__device__ __forceinline__ void st_acc(uint32_t row, int sw, float (&a)[64]) {
#pragma unroll
  for (int e = 0; e < 8; e++)
    stsm(st_addr(row, sw, e), pack_bf16(a[8 * e], a[8 * e + 1]), pack_bf16(a[8 * e + 2], a[8 * e + 3]),
         pack_bf16(a[8 * e + 4], a[8 * e + 5]), pack_bf16(a[8 * e + 6], a[8 * e + 7]));
}
__device__ __forceinline__ void st_o(uint32_t row, int sw, float (&a)[64], float l0, float l1) {
#pragma unroll
  for (int e = 0; e < 8; e++)
    stsm(st_addr(row, sw, e), pack_bf16(a[8 * e] * l0, a[8 * e + 1] * l0), pack_bf16(a[8 * e + 2] * l1, a[8 * e + 3] * l1),
         pack_bf16(a[8 * e + 4] * l0, a[8 * e + 5] * l0), pack_bf16(a[8 * e + 6] * l1, a[8 * e + 7] * l1));
}

template <int T, class Issue, class Shadow>
__device__ __forceinline__ void block(const Ctx& c, Issue issue, Shadow shadow) {
  blk_begin<T>(c);
  WG_FENCE();
  issue(tile_addr<T>(c));
  WG_COMMIT();
  if (T < 39 || c.wg == 0) turn_pass(c.wg);
  constexpr bool HAS_SHADOW = !(T == 8 || T == 14 || T == 15 || T == 24 || T == 29 || (T > 30 && T != 34 && T != 37 && T != 39));
  if (HAS_SHADOW) {
    SCHED_FENCE();
    shadow();
    SCHED_FENCE();
  }
  WG_WAIT(0);
}

template <int T0, int NF, class SShadow, class Fill, class After, class PvShadow>
__device__ __forceinline__ void head(const Ctx& c, uint32_t (&q)[32], float (&sc)[64], float& l0, float& l1, SShadow sshadow, Fill fill,
                                     After after, PvShadow pvshadow) {
  constexpr bool FRESH = (T0 == 8);
  float n0, n1;
  l0 = 0.f;
  l1 = 0.f;
  fence_frag<32, 0>(q);
  if (!FRESH) fence_acc(sc);
  block<T0>(c, [&](uint32_t a) { issue_s(sc, q, a, FRESH ? 0 : c.z); }, sshadow);
  fence_acc(sc);
  fence_frag<32, 0>(q);
  blk_release<T0>(c);
  softmax_max(sc, n0, n1);
  constexpr int E1 = (NF == 2) ? SEG2A : SEG3A, E2 = (NF == 2) ? 16 : SEG3B;
  block<T0 + 1>(c, [&](uint32_t a) { fill(0, a); }, [&]() {
    softmax_max_finish(n0, n1);
    softmax_exp<0, E1>(sc, q, n0, n1, l0, l1);
  });
  blk_release<T0 + 1>(c);
  after(0);
  block<T0 + 2>(c, [&](uint32_t a) { fill(1, a); }, [&]() { softmax_exp<E1, E2>(sc, q, n0, n1, l0, l1); });
  blk_release<T0 + 2>(c);
  after(1);
  if constexpr (NF == 3) {
    block<T0 + 3>(c, [&](uint32_t a) { fill(2, a); }, [&]() { softmax_exp<E2, 16>(sc, q, n0, n1, l0, l1); });
    blk_release<T0 + 3>(c);
    after(2);
  }
  fence_frag<32, 0>(q);
  fence_acc(sc);
  block<T0 + NF + 1>(c, [&](uint32_t a) { issue_nt(sc, q, a, c.z); }, [&]() {
    row_inv(l0, l1);
    asm volatile("" : "+f"(l0), "+f"(l1)::"memory");
    pvshadow();
  });
  fence_acc(sc);
  fence_frag<32, 0>(q);
  blk_release<T0 + NF + 1>(c);
}
__device__ __forceinline__ void o_frag(uint32_t (&f)[32], float (&a)[64], float l0, float l1) {
#pragma unroll
  for (int j = 0; j < 16; j++) {
    f[2 * j] = pack_bf16(a[4 * j] * l0, a[4 * j + 1] * l0);
    f[2 * j + 1] = pack_bf16(a[4 * j + 2] * l1, a[4 * j + 3] * l1);
  }
}

__global__ void __cluster_dims__(2, 1, 1) __launch_bounds__(384, 1) fused_attn_kernel(const __grid_constant__ Params p) {
  extern __shared__ uint8_t smem_raw[];
  const uint32_t sb = (smem_u32(smem_raw) + 1023) & ~1023u;
  const uint32_t bars = sb + NSLOT * SLOT;
  const int tid = threadIdx.x;
  const int warp = __shfl_sync(0xffffffffu, tid >> 5, 0);
  const int rank = blockIdx.x & 1;
  const int cid = blockIdx.x >> 1;
#define MAPV 1
  const int blk = cid >> 5, g = (cid >> 2) & 7, b = (cid & 3) * 2 + rank;

  const bool lead = elect_one();
  if (lead) {
    if (warp == 8) {
      PROF(40);
#pragma unroll
      for (int i = 0; i < 3; i++) mbar_init(bars + (FT + i) * 8, 1);
#pragma unroll
      for (int i = 0; i < 8; i++) mbar_init(bars + (FX + i) * 8, 1);
    } else {
#pragma unroll 1
      for (int i = 3 + warp - (warp > 8); i < NBAR; i += 11) {
        uint32_t cnt = 1;
        if (i >= SF && i < SE) cnt = 4;
        if (i >= ET && i < SF) cnt = (i < ET + 32 && ((LOCAL_ONLY >> (i - ET)) & 1)) ? 8 : 16;
        if (i < FX || i >= ET) mbar_init(bars + i * 8, cnt);
      }
    }
    asm volatile("fence.mbarrier_init.release.cluster;" ::: "memory");
  }
  __syncwarp();
  asm volatile("barrier.cluster.arrive.relaxed.aligned;" ::: "memory");

  if (warp >= 8) {
    asm volatile("setmaxnreg.dec.sync.aligned.u32 40;");
    if (warp == 8) {
      const CUtensorMap* tw = &p.wq[blk];
      const CUtensorMap* tk = &p.k[blk];
      const CUtensorMap* tv = &p.v[blk];
      const CUtensorMap* tu = &p.wo[blk];
      if (lead) {
#define NNOMC 3
#define XAHEAD 0
#pragma unroll 1
        for (int s = 0; s < NNOMC; s++) {
          mbar_expect_tx(bars + (FT + s) * 8, SLOT);
          tma_3d(sb + (4 + s) * SLOT, tw, 0, s * 64, g * 8, bars + (FT + s) * 8);
          tma_3d(sb + (4 + s) * SLOT + 16384, tw, 0, s * 64, g * 8 + 2, bars + (FT + s) * 8);
          mbar_expect_tx(bars + (FX + s) * 8, 16384);
          tma_2d(sb + s * 16384, &p.x[blk], s * 64, b * 128, bars + (FX + s) * 8);
          if (s == 0) PROF(53);
        }
#pragma unroll 1
        for (int s = NNOMC; s < NNOMC + XAHEAD; s++) {
          mbar_expect_tx(bars + (FX + s) * 8, 16384);
          tma_2d(sb + s * 16384, &p.x[blk], s * 64, b * 128, bars + (FX + s) * 8);
        }
        PROF(54);
      }
      __syncwarp();
      asm volatile("barrier.cluster.wait.acquire.aligned;" ::: "memory");
      if (lead) {
        PROF(55);
        const int kvrow = (b * 32 + g * 4) * 128;
        int nkv = 0, nq = 0, nu = 0;
#pragma unroll 1
        for (int t = NNOMC; t < 40; t++) {
          const int type = (t < 8) ? 4 : (int)((types_8_39() >> (2 * (t - 8))) & 3);
          const uint32_t dst = sb + tslot(t) * SLOT;
          const uint32_t fb = bars + (FT + t) * 8;
          if (t >= 3) mbar_wait(bars + (ET + tpred(t)) * 8);
          mbar_expect_tx(fb, SLOT);
          if (type == 4) {
            tma_3d_mc(dst + rank * 16384, tw, 0, t * 64, g * 8 + rank * 2, fb);
            if (t + XAHEAD < 8) {
              mbar_expect_tx(bars + (FX + t + XAHEAD) * 8, 16384);
              tma_2d(sb + (t + XAHEAD) * 16384, &p.x[blk], (t + XAHEAD) * 64, b * 128, bars + (FX + t + XAHEAD) * 8);
            }
          } else if (type < 2) {
            tma_3d(dst, type ? tv : tk, 0, kvrow + (nkv >> 1) * 128, 0, fb);
            nkv++;
          } else if (type == 2) {
            tma_2d_mc(dst + rank * 16384, &p.wq2[blk], g * 512 + 256 + (nq >> 2) * 128 + rank * 64, (nq & 3) * 128, fb);
            nq++;
          } else {
            const int ch = (int)(ULIST >> (4 * nu)) & 0xF;
            tma_2d_mc(dst + rank * 16384, tu, (((ch >> 2) + g) & 3) * 128 + rank * 64, g * 512 + (ch & 3) * 128, fb);
            nu++;
          }
          if (t >= 27 && t <= 30) mbar_arrive(bars + (RG + t - 27) * 8);
          if (t >= 34) mbar_arrive(bars + (RG + t - 30) * 8);
        }
        PROF(41);
      }
    } else if (warp == 11) {
      asm volatile("barrier.cluster.wait.acquire.aligned;" ::: "memory");
      const int lane = tid & 31;
#define ZT 10
      mbar_wait(bars + (FT + ZT) * 8);
      char* o = p.out_ptr + (size_t)(b * 128) * 2048 + blk * 1024 + g * 128;
#define ZSLEEP 64
#pragma unroll 1
      for (int i = 0; i < 32; i++) {
        const int e = i * 32 + lane;
        *reinterpret_cast<uint4*>(o + (size_t)(e >> 3) * 2048 + (e & 7) * 16) = make_uint4(0, 0, 0, 0);
        __nanosleep(ZSLEEP);
      }
      __syncwarp();
      if (lead) {
        unsigned int* cnt = &g_zero_cnt[(blk * 8 + b) * 32];
        unsigned int old;
        asm volatile("fence.acq_rel.gpu;" ::: "memory");
        asm volatile("atom.relaxed.gpu.global.add.u32 %0, [%1], 1;" : "=r"(old) : "l"(cnt) : "memory");
        const unsigned int target = (old & ~7u) + 8;
        unsigned int cur;
        int it = 0;
        do {
          asm volatile("ld.acquire.gpu.global.u32 %0, [%1];" : "=r"(cur) : "l"(cnt) : "memory");
          if (++it > (1 << 22)) __trap();
          if ((int)(cur - target) < 0) __nanosleep(200);
        } while ((int)(cur - target) < 0);
        asm volatile("fence.proxy.async;" ::: "memory");
        asm volatile("prefetch.tensormap [%0];" ::"l"(&p.out) : "memory");
#pragma unroll 1
        for (int i = 0; i < 4 * NFLUSH; i++) {
          const int hf = i & 1, w = (i >> 1) & 1, f = i >> 2;
          if (hf == 0) mbar_wait(bars + (SF + (i >> 1)) * 8);
          if (i < 10) mbar_wait(bars + (RG + i) * 8);
          asm volatile("cp.reduce.async.bulk.tensor.2d.global.shared::cta.add.tile.bulk_group [%0, {%2, %3}], [%1];" ::"l"(&p.out),
                       "r"(sb + 3 * SLOT + w * 8192 + hf * 16384), "r"(blk * 512 + ((((0x30210 >> (4 * f)) & 3) + g) & 3) * 128 + hf * 64),
                       "r"(b * 128 + w * 64)
                       : "memory");
          if (hf == 1) {
            asm volatile("cp.async.bulk.commit_group;" ::: "memory");
            if (f < 4) {
              asm volatile("cp.async.bulk.wait_group.read 0;" ::: "memory");
              mbar_arrive(bars + (SE + (i >> 1)) * 8);
            }
          }
        }
        asm volatile("cp.async.bulk.wait_group.read 0;" ::: "memory");
      }
    } else {
      const int i = tid - 288;
      uint32_t acc = 0;
#define TDEPTH 2
      {
        const char* w = p.wq_ptr[blk] + g * 1024;
        asm volatile("barrier.cluster.wait.acquire.aligned;" ::: "memory");
        {
          uint32_t v[3];
#pragma unroll
          for (int n = 0; n < 2; n++) {
            const int q = i >> 4, r = i & 15;
            const int code = (0x776D5C43 >> (4 * (n * 4 + q))) & 0xF;
            const char* a;
            if (code < 8) a = w + (size_t)(code * 64 + b * 8 + (r >> 1)) * 8192 + (r & 1) * 256;
            else a = p.x_ptr[blk] + (size_t)(b * 128 + g * 16 + r) * 1024 + (code - 10) * 256;
#define TW0 0
#define TW1 2
            if ((n == 0 ? TW0 : TW1) >= 0) mbar_wait(bars + (FT + (n == 0 ? TW0 : TW1)) * 8);
            asm volatile("ld.global.cg.L2::256B.u32 %0, [%1];" : "=r"(v[n + 1]) : "l"(a) : "memory");
          }
          const char* kp = p.k_ptr[blk] + (size_t)(b * 32 + g * 4) * 32768 + i * 256;
          const char* vp = p.v_ptr[blk] + (size_t)(b * 32 + g * 4) * 32768 + i * 256;
          constexpr uint64_t RT = (2ull << 4) | (5ull << 6) | (2ull << 10) | (5ull << 16) | (3ull << 24) | (5ull << 26) | (3ull << 34) |
                                  (5ull << 36) | (15ull << 40);
          int nk = 0, nv = 0, nq = 0, nu = 0;
          uint32_t u[TDEPTH];
#pragma unroll
          for (int q = 0; q < TDEPTH; q++) u[q] = (q < 2) ? v[1 + q] : 0;
#pragma unroll 1
          for (int n0 = 0; n0 < 22; n0 += TDEPTH) {
#pragma unroll
            for (int q = 0; q < TDEPTH; q++) {
              const int n = n0 + q;
              const int type = (int)((RT >> (2 * n)) & 3);
              const char* a;
              if (type == 0) a = kp + (nk++) * 16384;
              else if (type == 1) a = vp + (nv++) * 16384;
              else if (type == 2) a = w + (size_t)(i * 8 + b) * 8192 + 512 + (nq++) * 256;
              else a = p.wo_ptr[blk] + (size_t)(g * 512 + i * 8 + b) * 1024 + (((nu++) + g) & 3) * 256;
              acc ^= u[q];
              if (n < 22) asm volatile("ld.global.cg.L2::256B.u32 %0, [%1];" : "=r"(u[q]) : "l"(a) : "memory");
              if (warp == 9 && (n & 3) == 3) PROFW(42 + (n >> 2));
            }
          }
#pragma unroll
          for (int q = 0; q < TDEPTH; q++) acc ^= u[q];
        }
      }
      if (acc == 0x9e3779b9u && p.zero) g_zero_cnt[1] = acc;
    }
  } else {
    asm volatile("setmaxnreg.inc.sync.aligned.u32 232;");
    const int wg = warp >> 2;
    const int lane = tid & 31;
    uint32_t rel_base;
    asm volatile("mapa.shared::cluster.u32 %0, %1, %2;" : "=r"(rel_base) : "r"(bars), "r"(rank ^ (lane & 1)));
    if (wg == 1) turn_pass(1);
    asm volatile("barrier.cluster.wait.acquire.aligned;" ::: "memory");
    PROF(wg * 20 + 0);
    const Ctx c{sb, bars, rel_base, wg, (int)p.zero};
    const uint32_t xw = sb + wg * 8192;
    uint32_t c0[32], c1[32];
    {
      float acc[128];
      int slot = 4;
#pragma unroll 1
      for (int t = 0; t < 8; t++) {
        mbar_wait(bars + (FX + t) * 8);
        mbar_wait(bars + (FT + t) * 8);
        const uint64_t da = mkdesc(xw + t * 16384, 16, 1024);
        const uint64_t db = mkdesc(sb + slot * SLOT, 8192, 1024);
        turn_wait(wg);
        fence_acc(acc);
        WG_FENCE();
#pragma unroll
        for (int j = 0; j < 4; j++) wgmma_ss_n256_tb1(acc, da + j * 2, db + j * 128, j != 0 || t != 0);
        WG_COMMIT();
        turn_pass(wg);
        WG_WAIT(0);
        fence_acc(acc);
        FINE(t, 4);
        release(rel_base, ET + t, t == 5 ? 1 : 2);
        slot = (slot == 6) ? 4 : slot + 1;
      }
#pragma unroll
      for (int i = 0; i < 32; i++) {
        c0[i] = pack_bf16(acc[2 * i], acc[2 * i + 1]);
        c1[i] = pack_bf16(acc[64 + 2 * i], acc[64 + 2 * i + 1]);
      }
    }
    const int srow = (lane & 7) + ((lane >> 3) & 1) * 8;
    const uint32_t prow = sb + warp * 2048 + srow * 128;
    const int sw = (lane >> 4) ^ (lane & 7);
    auto nop = []() {};
    auto flush = [&](float(&a)[64], int f) {
      if (f >= 1) mbar_wait(bars + (SE + 2 * (f - 1) + wg) * 8);
      st_acc(prow + 3 * SLOT, sw, a);
      proxy_fence();
      __syncwarp();
      if (lead) mbar_arrive(bars + (SF + 2 * f + wg) * 8);
    };
    float ba[64];
    float bb[64];
    float l0, l1;
    head<8, 3>(c, c0, ba, l0, l1, nop, [&](int i, uint32_t a) { issue_q(bb, xw + i * SLOT, a, i != 0); }, [&](int) { fence_acc(bb); }, nop);
    block<13>(c, [&](uint32_t a) { issue_q(bb, xw + 3 * SLOT, a, 1); }, [&]() { o_frag(c0, ba, l0, l1); fence_frag<32, 0>(c0); });
    fence_acc(bb);
    blk_release<13>(c);
    fence_acc(ba);
    block<14>(c, [&](uint32_t a) { issue_q(ba, xw, a, c.z); }, nop);
    fence_acc(ba);
    blk_release<14>(c);
    st_frag(prow, sw, c0);
    cvt_frag(c0, bb);
    head<15, 3>(c, c1, bb, l0, l1, nop, [&](int i, uint32_t a) { issue_q(ba, xw + (i + 1) * SLOT, a, 1); }, [&](int) { fence_acc(ba); }, nop);
    st_o(prow + SLOT, sw, bb, l0, l1);
    head<20, 2>(c, c0, bb, l0, l1,
                [&]() {
                  proxy_fence();
                  cvt_frag(c1, ba);
                  fence_frag<32, 0>(c1);
                  fence_acc(ba);
                },
                [&](int i, uint32_t a) { issue_q(ba, xw + i * SLOT, a, i ? 1 : c.z); }, [&](int i) { fence_acc(ba); },
                [&]() { flush(ba, 0); });
    o_frag(c0, bb, l0, l1);
    fence_acc(ba);
    head<24, 3>(c, c1, bb, l0, l1, nop,
                [&](int i, uint32_t a) {
                  if (i < 2) issue_q(ba, xw + i * SLOT, a, i ? 1 : c.z);
                  else issue_nt(ba, c0, a, 1);
                },
                [&](int i) { fence_acc(ba); fence_frag<32, 0>(c0); }, nop);
    o_frag(c1, bb, l0, l1);
    fence_frag<32, 0>(c1);
    fence_acc(bb);
    block<29>(c, [&](uint32_t a) { issue_nt(ba, c1, a, 1); }, nop);
    fence_acc(ba);
    blk_release<29>(c);
    block<30>(c, [&](uint32_t a) { issue_q(bb, xw, a, c.z); }, [&]() { flush(ba, 1); });
    blk_release<30>(c);
    block<31>(c, [&](uint32_t a) { issue_q(bb, xw + SLOT, a, 1); }, nop);
    blk_release<31>(c);
    block<32>(c, [&](uint32_t a) { issue_nt(bb, c0, a, 1); }, nop);
    blk_release<32>(c);
    block<33>(c, [&](uint32_t a) { issue_nt(bb, c1, a, 1); }, nop);
    fence_acc(bb);
    fence_acc(ba);
    blk_release<33>(c);
    block<34>(c, [&](uint32_t a) { issue_q(ba, xw, a, c.z); }, [&]() { flush(bb, 2); });
    blk_release<34>(c);
    fence_acc(bb);
    block<35>(c, [&](uint32_t a) { issue_nt(bb, c0, a, c.z); }, nop);
    blk_release<35>(c);
    block<36>(c, [&](uint32_t a) { issue_nt(bb, c1, a, 1); }, nop);
    fence_acc(bb);
    blk_release<36>(c);
    block<37>(c, [&](uint32_t a) { issue_q(ba, xw + SLOT, a, 1); }, [&]() { flush(bb, 3); });
    blk_release<37>(c);
    block<38>(c, [&](uint32_t a) { issue_nt(ba, c0, a, 1); }, nop);
    blk_release<38>(c);
    block<39>(c, [&](uint32_t a) { issue_nt(ba, c1, a, 1); }, [&]() { mbar_wait(bars + (SE + 6 + wg) * 8); });
    fence_acc(ba);
    blk_release<39>(c);
    st_acc(prow + 3 * SLOT, sw, ba);
    proxy_fence();
    __syncwarp();
    if (lead) mbar_arrive(bars + (SF + 8 + wg) * 8);
  }
}

typedef CUresult (*EncodeFn)(CUtensorMap*, CUtensorMapDataType, cuuint32_t, void*, const cuuint64_t*, const cuuint64_t*,
                             const cuuint32_t*, const cuuint32_t*, CUtensorMapInterleave, CUtensorMapSwizzle,
                             CUtensorMapL2promotion, CUtensorMapFloatOOBfill);

void encode(EncodeFn fn, CUtensorMap* m, const void* ptr, int rank, const cuuint64_t* dims, const cuuint64_t* strides,
            const cuuint32_t* box) {
  cuuint32_t es[3] = {1, 1, 1};
  fn(m, CU_TENSOR_MAP_DATA_TYPE_BFLOAT16, rank, const_cast<void*>(ptr), dims, strides, box, es, CU_TENSOR_MAP_INTERLEAVE_NONE,
     CU_TENSOR_MAP_SWIZZLE_128B, CU_TENSOR_MAP_L2_PROMOTION_L2_256B, CU_TENSOR_MAP_FLOAT_OOB_FILL_NONE);
}

}

extern "C" void kernel_launch(void* const* d_in, const int* in_sizes, int n_in, void* d_out, int out_size) {
  (void)in_sizes; (void)n_in; (void)out_size;
  static EncodeFn fn = nullptr;
  if (!fn) {
    void* f = nullptr;
    cudaDriverEntryPointQueryResult qr;
    cudaGetDriverEntryPoint("cuTensorMapEncodeTiled", &f, cudaEnableDefault, &qr);
    fn = (EncodeFn)f;
    cudaFuncSetAttribute(fused_attn_kernel, cudaFuncAttributeMaxDynamicSharedMemorySize, SMEM_BYTES);
  }
  Params p;
  for (int i = 0; i < 2; i++) {
    const void* x = d_in[i * 5 + 0];
    const void* k = d_in[i * 5 + 1];
    const void* v = d_in[i * 5 + 2];
    const void* wq = d_in[i * 5 + 3];
    const void* wo = d_in[i * 5 + 4];
    {
      cuuint64_t d[2] = {512, 1024}, s[1] = {1024};
      cuuint32_t bx[2] = {64, 128};
      encode(fn, &p.x[i], x, 2, d, s, bx);
    }
    {
      cuuint64_t d[3] = {64, 512, 64}, s[2] = {8192, 128};
      cuuint32_t bx[3] = {64, 64, 2};
      encode(fn, &p.wq[i], wq, 3, d, s, bx);
    }
    {
      cuuint64_t d[2] = {4096, 512}, s[1] = {8192};
      cuuint32_t bx[2] = {64, 128};
      encode(fn, &p.wq2[i], wq, 2, d, s, bx);
    }
    {
      cuuint64_t d[3] = {64, 32768, 2}, s[2] = {256, 128};
      cuuint32_t bx[3] = {64, 128, 2};
      encode(fn, &p.k[i], k, 3, d, s, bx);
      encode(fn, &p.v[i], v, 3, d, s, bx);
    }
    {
      cuuint64_t d[2] = {512, 4096}, s[1] = {1024};
      cuuint32_t bx[2] = {64, 128};
      encode(fn, &p.wo[i], wo, 2, d, s, bx);
    }
    p.x_ptr[i] = (const char*)x;
    p.wq_ptr[i] = (const char*)wq;
    p.k_ptr[i] = (const char*)k;
    p.v_ptr[i] = (const char*)v;
    p.wo_ptr[i] = (const char*)wo;
  }
  {
    cuuint64_t d[2] = {1024, 1024}, s[1] = {2048};
    cuuint32_t bx[2] = {64, 64};
    encode(fn, &p.out, d_out, 2, d, s, bx);
  }
  p.out_ptr = (char*)d_out;
  p.zero = 0;
  fused_attn_kernel<<<128, 384, SMEM_BYTES, cudaStreamPerThread>>>(p);
}
```

```cpp
#include <cuda_runtime.h>
#include <cuda_bf16.h>
#include <cuda.h>
#include <stdint.h>

namespace {

constexpr int SLOT = 32768;
constexpr int NSLOT = 7;
constexpr int SMEM_BYTES = NSLOT * SLOT + 1024   + 1024  ;
constexpr int FT = 0;
constexpr int FX = 40;
constexpr int ET = 48;
constexpr int SF = 84;
constexpr int SE = 100;
constexpr int FA = 108;
constexpr int NBAR = 109;
__host__ __device__ constexpr int ttype(int t) {
  return t < 8 ? 4 : (t == 8 || t == 15 || t == 20 || t == 25) ? 0 : (t == 12 || t == 19 || t == 23 || t == 29) ? 1 : (t < 19 ? 2 : 3);
}
__host__ __device__ constexpr uint64_t types_8_39() {
  uint64_t r = 0;
  for (int t = 8; t < 40; t++) r |= (uint64_t)ttype(t) << (2 * (t - 8));
  return r;
}
__host__ __device__ constexpr int tslot(int t) { return t < 20 ? 4 + t % 3 : (0x5462 >> (4 * (t & 3))) & 0xF; }
__host__ __device__ constexpr int tpred(int t) { return t < 21 ? t - 3 : t - 4; }
__host__ __device__ constexpr uint32_t local_only() {
  uint32_t r = 0xFFFFFFFFu;
  for (int t = 3; t < 36; t++)
    if (ttype(t) >= 2) r &= ~(1u << tpred(t));
  return r;
}
constexpr uint32_t LOCAL_ONLY = local_only();
constexpr uint64_t ULIST = 0xDCBA9837654210ull;

struct Params {
  CUtensorMap x[2], wq[2], wq2[2], k[2], v[2], wo[2], out;
  const char* x_ptr[2];
  const char* wq_ptr[2];
  const char* k_ptr[2];
  const char* v_ptr[2];
  const char* wo_ptr[2];
  char* out_ptr;
  uint32_t zero;
};

__device__ unsigned int g_zero_cnt[16 * 32];
#define PROF(idx) do {} while (0)
#define PROFW(idx) do {} while (0)
#define FINE(blk, ev) do {} while (0)

__device__ __forceinline__ uint32_t smem_u32(const void* p) { return (uint32_t)__cvta_generic_to_shared(p); }
__device__ __forceinline__ bool elect_one() {
  uint32_t r;
  asm volatile("{\n.reg .pred p;\nelect.sync _|p, 0xffffffff;\nselp.u32 %0, 1, 0, p;\n}" : "=r"(r));
  return r;
}
__device__ __forceinline__ void mbar_init(uint32_t bar, uint32_t cnt) {
  asm volatile("mbarrier.init.shared::cta.b64 [%0], %1;" ::"r"(bar), "r"(cnt) : "memory");
}
__device__ __forceinline__ void mbar_expect_tx(uint32_t bar, uint32_t bytes) {
  asm volatile("mbarrier.arrive.expect_tx.shared::cta.b64 _, [%0], %1;" ::"r"(bar), "r"(bytes) : "memory");
}
__device__ __forceinline__ void mbar_arrive(uint32_t bar) {
  asm volatile("mbarrier.arrive.shared::cta.b64 _, [%0];" ::"r"(bar) : "memory");
}
__device__ __forceinline__ void mbar_arrive_cluster(uint32_t bar_cluster_addr) {
  asm volatile("mbarrier.arrive.shared::cluster.b64 _, [%0];" ::"r"(bar_cluster_addr) : "memory");
}
__device__ __forceinline__ void mbar_wait(uint32_t bar) {
  asm volatile(
      "{\n.reg .pred p;\n.reg .b32 n;\nmov.u32 n, 0;\n"
      "WAIT_LOOP:\n"
      "mbarrier.try_wait.parity.shared::cta.b64 p, [%0], 0;\n"
      "@p bra WAIT_DONE;\n"
      "add.u32 n, n, 1;\n"
      "setp.lt.u32 p, n, 0x1000000;\n"
      "@p bra WAIT_LOOP;\n"
      "trap;\n"
      "WAIT_DONE:\n}" ::"r"(bar) : "memory");
}
__device__ __forceinline__ void tma_2d(uint32_t dst, const CUtensorMap* tm, int c0, int c1, uint32_t bar) {
  asm volatile("cp.async.bulk.tensor.2d.shared::cluster.global.mbarrier::complete_tx::bytes [%0], [%1, {%3, %4}], [%2];"
               ::"r"(dst), "l"(tm), "r"(bar), "r"(c0), "r"(c1) : "memory");
}
__device__ __forceinline__ void tma_3d(uint32_t dst, const CUtensorMap* tm, int c0, int c1, int c2, uint32_t bar) {
  asm volatile("cp.async.bulk.tensor.3d.shared::cluster.global.mbarrier::complete_tx::bytes [%0], [%1, {%3, %4, %5}], [%2];"
               ::"r"(dst), "l"(tm), "r"(bar), "r"(c0), "r"(c1), "r"(c2) : "memory");
}
__device__ __forceinline__ void tma_3d_hint(uint32_t dst, const CUtensorMap* tm, int c0, int c1, int c2, uint32_t bar, uint64_t pol) {
  asm volatile("cp.async.bulk.tensor.3d.shared::cluster.global.mbarrier::complete_tx::bytes.L2::cache_hint [%0], [%1, {%3, %4, %5}], [%2], %6;"
               ::"r"(dst), "l"(tm), "r"(bar), "r"(c0), "r"(c1), "r"(c2), "l"(pol) : "memory");
}
__device__ __forceinline__ void tma_2d_mc(uint32_t dst, const CUtensorMap* tm, int c0, int c1, uint32_t bar) {
  asm volatile("cp.async.bulk.tensor.2d.shared::cluster.global.mbarrier::complete_tx::bytes.multicast::cluster [%0], [%1, {%3, %4}], [%2], %5;"
               ::"r"(dst), "l"(tm), "r"(bar), "r"(c0), "r"(c1), "h"((uint16_t)3) : "memory");
}
__device__ __forceinline__ void tma_3d_mc(uint32_t dst, const CUtensorMap* tm, int c0, int c1, int c2, uint32_t bar) {
  asm volatile("cp.async.bulk.tensor.3d.shared::cluster.global.mbarrier::complete_tx::bytes.multicast::cluster [%0], [%1, {%3, %4, %5}], [%2], %6;"
               ::"r"(dst), "l"(tm), "r"(bar), "r"(c0), "r"(c1), "r"(c2), "h"((uint16_t)3) : "memory");
}
constexpr uint32_t DK = 1u << 16;
constexpr uint32_t DN = (16384u >> 4) << 16;
constexpr uint32_t DW = (4096u >> 4) << 16;
constexpr int SLOT16 = SLOT >> 4;
__device__ __forceinline__ uint32_t pack_bf16(float lo, float hi) {
  uint32_t r;
  asm("cvt.rn.bf16x2.f32 %0, %1, %2;" : "=r"(r) : "f"(hi), "f"(lo));
  return r;
}
__device__ __forceinline__ float ex2(float x) {
  float r;
  asm("ex2.approx.ftz.f32 %0, %1;" : "=f"(r) : "f"(x));
  return r;
}
#define SCHED_FENCE() mbar_wait(c.bars + FX * 8)
#define WG_FENCE() asm volatile("wgmma.fence.sync.aligned;" ::: "memory")
#define WG_COMMIT() asm volatile("wgmma.commit_group.sync.aligned;" ::: "memory")
#define WG_WAIT(n) asm volatile("wgmma.wait_group.sync.aligned %0;" ::"n"(n) : "memory")
template <int N>
__device__ __forceinline__ void fence_acc(float (&d)[N]) {
#pragma unroll
  for (int i = 0; i < N; i++) asm volatile("" : "+f"(d[i])::"memory");
}
template <int N, int OFF, int TOT>
__device__ __forceinline__ void fence_frag(uint32_t (&d)[TOT]) {
#pragma unroll
  for (int i = 0; i < N; i++) asm volatile("" : "+r"(d[OFF + i])::"memory");
}

__device__ __forceinline__ void wgmma_ss_n256_tb1(float (&d)[128], uint32_t da, uint32_t db, int scale_d) {
  asm volatile("{\n.reg .pred p;\n.reg .b64 a, b;\nsetp.ne.b32 p, %130, 0;\nmov.b64 a, {%128, 0x40000040};\nmov.b64 b, {%129, 0x40000040};\n"
      "wgmma.mma_async.sync.aligned.m64n256k16.f32.bf16.bf16 {"
      "%0, %1, %2, %3, %4, %5, %6, %7, %8, %9, %10, %11, %12, %13, %14, %15, %16, %17, %18, %19, %20, %21, %22, %23, %24, %25, %26, %27, %28, %29, %30, %31, "
      "%32, %33, %34, %35, %36, %37, %38, %39, %40, %41, %42, %43, %44, %45, %46, %47, %48, %49, %50, %51, %52, %53, %54, %55, %56, %57, %58, %59, %60, %61, %62, %63, "
      "%64, %65, %66, %67, %68, %69, %70, %71, %72, %73, %74, %75, %76, %77, %78, %79, %80, %81, %82, %83, %84, %85, %86, %87, %88, %89, %90, %91, %92, %93, %94, %95, "
      "%96, %97, %98, %99, %100, %101, %102, %103, %104, %105, %106, %107, %108, %109, %110, %111, %112, %113, %114, %115, %116, %117, %118, %119, %120, %121, %122, %123, %124, %125, %126, %127"
      "}, a, b, p, 1, 1, 0, 1;\n}\n"
    :
      "+f"(d[0]), "+f"(d[1]), "+f"(d[2]), "+f"(d[3]), "+f"(d[4]), "+f"(d[5]), "+f"(d[6]), "+f"(d[7]),
      "+f"(d[8]), "+f"(d[9]), "+f"(d[10]), "+f"(d[11]), "+f"(d[12]), "+f"(d[13]), "+f"(d[14]), "+f"(d[15]),
      "+f"(d[16]), "+f"(d[17]), "+f"(d[18]), "+f"(d[19]), "+f"(d[20]), "+f"(d[21]), "+f"(d[22]), "+f"(d[23]),
      "+f"(d[24]), "+f"(d[25]), "+f"(d[26]), "+f"(d[27]), "+f"(d[28]), "+f"(d[29]), "+f"(d[30]), "+f"(d[31]),
      "+f"(d[32]), "+f"(d[33]), "+f"(d[34]), "+f"(d[35]), "+f"(d[36]), "+f"(d[37]), "+f"(d[38]), "+f"(d[39]),
      "+f"(d[40]), "+f"(d[41]), "+f"(d[42]), "+f"(d[43]), "+f"(d[44]), "+f"(d[45]), "+f"(d[46]), "+f"(d[47]),
      "+f"(d[48]), "+f"(d[49]), "+f"(d[50]), "+f"(d[51]), "+f"(d[52]), "+f"(d[53]), "+f"(d[54]), "+f"(d[55]),
      "+f"(d[56]), "+f"(d[57]), "+f"(d[58]), "+f"(d[59]), "+f"(d[60]), "+f"(d[61]), "+f"(d[62]), "+f"(d[63]),
      "+f"(d[64]), "+f"(d[65]), "+f"(d[66]), "+f"(d[67]), "+f"(d[68]), "+f"(d[69]), "+f"(d[70]), "+f"(d[71]),
      "+f"(d[72]), "+f"(d[73]), "+f"(d[74]), "+f"(d[75]), "+f"(d[76]), "+f"(d[77]), "+f"(d[78]), "+f"(d[79]),
      "+f"(d[80]), "+f"(d[81]), "+f"(d[82]), "+f"(d[83]), "+f"(d[84]), "+f"(d[85]), "+f"(d[86]), "+f"(d[87]),
      "+f"(d[88]), "+f"(d[89]), "+f"(d[90]), "+f"(d[91]), "+f"(d[92]), "+f"(d[93]), "+f"(d[94]), "+f"(d[95]),
      "+f"(d[96]), "+f"(d[97]), "+f"(d[98]), "+f"(d[99]), "+f"(d[100]), "+f"(d[101]), "+f"(d[102]), "+f"(d[103]),
      "+f"(d[104]), "+f"(d[105]), "+f"(d[106]), "+f"(d[107]), "+f"(d[108]), "+f"(d[109]), "+f"(d[110]), "+f"(d[111]),
      "+f"(d[112]), "+f"(d[113]), "+f"(d[114]), "+f"(d[115]), "+f"(d[116]), "+f"(d[117]), "+f"(d[118]), "+f"(d[119]),
      "+f"(d[120]), "+f"(d[121]), "+f"(d[122]), "+f"(d[123]), "+f"(d[124]), "+f"(d[125]), "+f"(d[126]), "+f"(d[127])
    : "r"(da), "r"(db), "r"(scale_d));
}
__device__ __forceinline__ void wgmma_ss_n128_tb1(float (&d)[64], uint32_t da, uint32_t db, int scale_d) {
  asm volatile("{\n.reg .pred p;\n.reg .b64 a, b;\nsetp.ne.b32 p, %66, 0;\nmov.b64 a, {%64, 0x40000040};\nmov.b64 b, {%65, 0x40000040};\n"
      "wgmma.mma_async.sync.aligned.m64n128k16.f32.bf16.bf16 {"
      "%0, %1, %2, %3, %4, %5, %6, %7, %8, %9, %10, %11, %12, %13, %14, %15, %16, %17, %18, %19, %20, %21, %22, %23, %24, %25, %26, %27, %28, %29, %30, %31, "
      "%32, %33, %34, %35, %36, %37, %38, %39, %40, %41, %42, %43, %44, %45, %46, %47, %48, %49, %50, %51, %52, %53, %54, %55, %56, %57, %58, %59, %60, %61, %62, %63"
      "}, a, b, p, 1, 1, 0, 1;\n}\n"
    :
      "+f"(d[0]), "+f"(d[1]), "+f"(d[2]), "+f"(d[3]), "+f"(d[4]), "+f"(d[5]), "+f"(d[6]), "+f"(d[7]),
      "+f"(d[8]), "+f"(d[9]), "+f"(d[10]), "+f"(d[11]), "+f"(d[12]), "+f"(d[13]), "+f"(d[14]), "+f"(d[15]),
      "+f"(d[16]), "+f"(d[17]), "+f"(d[18]), "+f"(d[19]), "+f"(d[20]), "+f"(d[21]), "+f"(d[22]), "+f"(d[23]),
      "+f"(d[24]), "+f"(d[25]), "+f"(d[26]), "+f"(d[27]), "+f"(d[28]), "+f"(d[29]), "+f"(d[30]), "+f"(d[31]),
      "+f"(d[32]), "+f"(d[33]), "+f"(d[34]), "+f"(d[35]), "+f"(d[36]), "+f"(d[37]), "+f"(d[38]), "+f"(d[39]),
      "+f"(d[40]), "+f"(d[41]), "+f"(d[42]), "+f"(d[43]), "+f"(d[44]), "+f"(d[45]), "+f"(d[46]), "+f"(d[47]),
      "+f"(d[48]), "+f"(d[49]), "+f"(d[50]), "+f"(d[51]), "+f"(d[52]), "+f"(d[53]), "+f"(d[54]), "+f"(d[55]),
      "+f"(d[56]), "+f"(d[57]), "+f"(d[58]), "+f"(d[59]), "+f"(d[60]), "+f"(d[61]), "+f"(d[62]), "+f"(d[63])
    : "r"(da), "r"(db), "r"(scale_d));
}
__device__ __forceinline__ void wgmma_rs_n128_tb0(float (&d)[64], uint32_t a0, uint32_t a1, uint32_t a2, uint32_t a3, uint32_t db, int scale_d) {
  asm volatile("{\n.reg .pred p;\n.reg .b64 b;\nsetp.ne.b32 p, %69, 0;\nmov.b64 b, {%68, 0x40000040};\n"
      "wgmma.mma_async.sync.aligned.m64n128k16.f32.bf16.bf16 {"
      "%0, %1, %2, %3, %4, %5, %6, %7, %8, %9, %10, %11, %12, %13, %14, %15, %16, %17, %18, %19, %20, %21, %22, %23, %24, %25, %26, %27, %28, %29, %30, %31, "
      "%32, %33, %34, %35, %36, %37, %38, %39, %40, %41, %42, %43, %44, %45, %46, %47, %48, %49, %50, %51, %52, %53, %54, %55, %56, %57, %58, %59, %60, %61, %62, %63"
      "}, {%64, %65, %66, %67}, b, p, 1, 1, 0;\n}\n"
    :
      "+f"(d[0]), "+f"(d[1]), "+f"(d[2]), "+f"(d[3]), "+f"(d[4]), "+f"(d[5]), "+f"(d[6]), "+f"(d[7]),
      "+f"(d[8]), "+f"(d[9]), "+f"(d[10]), "+f"(d[11]), "+f"(d[12]), "+f"(d[13]), "+f"(d[14]), "+f"(d[15]),
      "+f"(d[16]), "+f"(d[17]), "+f"(d[18]), "+f"(d[19]), "+f"(d[20]), "+f"(d[21]), "+f"(d[22]), "+f"(d[23]),
      "+f"(d[24]), "+f"(d[25]), "+f"(d[26]), "+f"(d[27]), "+f"(d[28]), "+f"(d[29]), "+f"(d[30]), "+f"(d[31]),
      "+f"(d[32]), "+f"(d[33]), "+f"(d[34]), "+f"(d[35]), "+f"(d[36]), "+f"(d[37]), "+f"(d[38]), "+f"(d[39]),
      "+f"(d[40]), "+f"(d[41]), "+f"(d[42]), "+f"(d[43]), "+f"(d[44]), "+f"(d[45]), "+f"(d[46]), "+f"(d[47]),
      "+f"(d[48]), "+f"(d[49]), "+f"(d[50]), "+f"(d[51]), "+f"(d[52]), "+f"(d[53]), "+f"(d[54]), "+f"(d[55]),
      "+f"(d[56]), "+f"(d[57]), "+f"(d[58]), "+f"(d[59]), "+f"(d[60]), "+f"(d[61]), "+f"(d[62]), "+f"(d[63])
    : "r"(a0), "r"(a1), "r"(a2), "r"(a3), "r"(db), "r"(scale_d));
}
__device__ __forceinline__ void wgmma_rs_n128_tb1(float (&d)[64], uint32_t a0, uint32_t a1, uint32_t a2, uint32_t a3, uint32_t db, int scale_d) {
  asm volatile("{\n.reg .pred p;\n.reg .b64 b;\nsetp.ne.b32 p, %69, 0;\nmov.b64 b, {%68, 0x40000040};\n"
      "wgmma.mma_async.sync.aligned.m64n128k16.f32.bf16.bf16 {"
      "%0, %1, %2, %3, %4, %5, %6, %7, %8, %9, %10, %11, %12, %13, %14, %15, %16, %17, %18, %19, %20, %21, %22, %23, %24, %25, %26, %27, %28, %29, %30, %31, "
      "%32, %33, %34, %35, %36, %37, %38, %39, %40, %41, %42, %43, %44, %45, %46, %47, %48, %49, %50, %51, %52, %53, %54, %55, %56, %57, %58, %59, %60, %61, %62, %63"
      "}, {%64, %65, %66, %67}, b, p, 1, 1, 1;\n}\n"
    :
      "+f"(d[0]), "+f"(d[1]), "+f"(d[2]), "+f"(d[3]), "+f"(d[4]), "+f"(d[5]), "+f"(d[6]), "+f"(d[7]),
      "+f"(d[8]), "+f"(d[9]), "+f"(d[10]), "+f"(d[11]), "+f"(d[12]), "+f"(d[13]), "+f"(d[14]), "+f"(d[15]),
      "+f"(d[16]), "+f"(d[17]), "+f"(d[18]), "+f"(d[19]), "+f"(d[20]), "+f"(d[21]), "+f"(d[22]), "+f"(d[23]),
      "+f"(d[24]), "+f"(d[25]), "+f"(d[26]), "+f"(d[27]), "+f"(d[28]), "+f"(d[29]), "+f"(d[30]), "+f"(d[31]),
      "+f"(d[32]), "+f"(d[33]), "+f"(d[34]), "+f"(d[35]), "+f"(d[36]), "+f"(d[37]), "+f"(d[38]), "+f"(d[39]),
      "+f"(d[40]), "+f"(d[41]), "+f"(d[42]), "+f"(d[43]), "+f"(d[44]), "+f"(d[45]), "+f"(d[46]), "+f"(d[47]),
      "+f"(d[48]), "+f"(d[49]), "+f"(d[50]), "+f"(d[51]), "+f"(d[52]), "+f"(d[53]), "+f"(d[54]), "+f"(d[55]),
      "+f"(d[56]), "+f"(d[57]), "+f"(d[58]), "+f"(d[59]), "+f"(d[60]), "+f"(d[61]), "+f"(d[62]), "+f"(d[63])
    : "r"(a0), "r"(a1), "r"(a2), "r"(a3), "r"(db), "r"(scale_d));
}
__device__ __forceinline__ void wgmma_rs_n64_tb1(float (&d)[32], uint32_t a0, uint32_t a1, uint32_t a2, uint32_t a3, uint32_t db, int scale_d) {
  asm volatile("{\n.reg .pred p;\n.reg .b64 b;\nsetp.ne.b32 p, %37, 0;\nmov.b64 b, {%36, 0x40000040};\n"
      "wgmma.mma_async.sync.aligned.m64n64k16.f32.bf16.bf16 {"
      "%0, %1, %2, %3, %4, %5, %6, %7, %8, %9, %10, %11, %12, %13, %14, %15, %16, %17, %18, %19, %20, %21, %22, %23, %24, %25, %26, %27, %28, %29, %30, %31"
      "}, {%32, %33, %34, %35}, b, p, 1, 1, 1;\n}\n"
    :
      "+f"(d[0]), "+f"(d[1]), "+f"(d[2]), "+f"(d[3]), "+f"(d[4]), "+f"(d[5]), "+f"(d[6]), "+f"(d[7]),
      "+f"(d[8]), "+f"(d[9]), "+f"(d[10]), "+f"(d[11]), "+f"(d[12]), "+f"(d[13]), "+f"(d[14]), "+f"(d[15]),
      "+f"(d[16]), "+f"(d[17]), "+f"(d[18]), "+f"(d[19]), "+f"(d[20]), "+f"(d[21]), "+f"(d[22]), "+f"(d[23]),
      "+f"(d[24]), "+f"(d[25]), "+f"(d[26]), "+f"(d[27]), "+f"(d[28]), "+f"(d[29]), "+f"(d[30]), "+f"(d[31])
    : "r"(a0), "r"(a1), "r"(a2), "r"(a3), "r"(db), "r"(scale_d));
}

__device__ __forceinline__ void turn_wait(int wg) { asm volatile("bar.sync %0, 256;" ::"r"(1 + wg) : "memory"); }
__device__ __forceinline__ void turn_pass(int wg) { asm volatile("bar.arrive %0, 256;" ::"r"(2 - wg) : "memory"); }

__device__ __forceinline__ void release(uint32_t rel_base, int idx, int nl) {
  if ((int)(threadIdx.x & 31) < nl) mbar_arrive_cluster(rel_base + idx * 8);
}

#define SEG2A 6
#define SEG3A 4
#define SEG3B 10
constexpr float SM_C = 0.08838834764831845f * 1.4426950408889634f;

__device__ __forceinline__ void issue_s(float (&sc)[64], uint32_t (&q)[32], uint32_t k16, int acc0) {
#pragma unroll
  for (int j = 0; j < 8; j++)
    wgmma_rs_n128_tb0(sc, q[4 * j], q[4 * j + 1], q[4 * j + 2], q[4 * j + 3], k16 + DK + (j >> 2) * 1024 + (j & 3) * 2, j != 0 ? 1 : acc0);
}
__device__ __forceinline__ void issue_nt(float (&d)[64], uint32_t (&a)[32], uint32_t b16, int acc0) {
#pragma unroll
  for (int j = 0; j < 8; j++)
    wgmma_rs_n128_tb1(d, a[4 * j], a[4 * j + 1], a[4 * j + 2], a[4 * j + 3], b16 + DN + j * 128, j != 0 ? 1 : acc0);
}
__device__ __forceinline__ void issue_q(float (&d)[64], uint32_t x16, uint32_t b16, int acc0) {
  asm volatile("" : "+r"(x16));
#pragma unroll
  for (int j = 0; j < 8; j++) wgmma_ss_n128_tb1(d, x16 + DK + (j >> 2) * 1024 + (j & 3) * 2, b16 + DN + j * 128, j != 0 ? 1 : acc0);
}
__device__ __forceinline__ void issue_nt64(float (&d)[32], uint32_t (&a)[32], uint32_t (&a2)[32], uint32_t b16) {
#pragma unroll
  for (int j = 0; j < 8; j++) wgmma_rs_n64_tb1(d, a[4 * j], a[4 * j + 1], a[4 * j + 2], a[4 * j + 3], b16 + DN + j * 128, j != 0);
#pragma unroll
  for (int j = 0; j < 8; j++) wgmma_rs_n64_tb1(d, a2[4 * j], a2[4 * j + 1], a2[4 * j + 2], a2[4 * j + 3], b16 + DN + 1024 + j * 128, 1);
}
__device__ __forceinline__ void softmax_max(float (&sc)[64], int& m0, int& m1) {
  int a0[4], a1[4];
#pragma unroll
  for (int q = 0; q < 4; q++) {
    a0[q] = max(__float_as_int(sc[16 * q]), __float_as_int(sc[16 * q + 1]));
    a1[q] = max(__float_as_int(sc[16 * q + 2]), __float_as_int(sc[16 * q + 3]));
#pragma unroll
    for (int j = 1; j < 4; j++) {
      a0[q] = __vimax3_s32(a0[q], __float_as_int(sc[16 * q + 4 * j]), __float_as_int(sc[16 * q + 4 * j + 1]));
      a1[q] = __vimax3_s32(a1[q], __float_as_int(sc[16 * q + 4 * j + 2]), __float_as_int(sc[16 * q + 4 * j + 3]));
    }
  }
  m0 = max(__vimax3_s32(a0[0], a0[1], a0[2]), a0[3]);
  m1 = max(__vimax3_s32(a1[0], a1[1], a1[2]), a1[3]);
  m0 = max(m0, __shfl_xor_sync(0xffffffffu, m0, 1));
  m1 = max(m1, __shfl_xor_sync(0xffffffffu, m1, 1));
  asm volatile("" : "+r"(m0), "+r"(m1)::"memory");
}
__device__ __forceinline__ void softmax_max_finish(float (&sc)[64], int m0, int m1, float& n0, float& n1) {
  m0 = max(m0, __shfl_xor_sync(0xffffffffu, m0, 2));
  m1 = max(m1, __shfl_xor_sync(0xffffffffu, m1, 2));
  n0 = __int_as_float(m0);
  n1 = __int_as_float(m1);
  if (__any_sync(0xffffffffu, (m0 | m1) < 0)) {
    n0 = fmaxf(sc[0], sc[1]);
    n1 = fmaxf(sc[2], sc[3]);
#pragma unroll
    for (int j = 1; j < 16; j++) {
      n0 = fmaxf(n0, fmaxf(sc[4 * j], sc[4 * j + 1]));
      n1 = fmaxf(n1, fmaxf(sc[4 * j + 2], sc[4 * j + 3]));
    }
    n0 = fmaxf(n0, __shfl_xor_sync(0xffffffffu, n0, 1));
    n1 = fmaxf(n1, __shfl_xor_sync(0xffffffffu, n1, 1));
    n0 = fmaxf(n0, __shfl_xor_sync(0xffffffffu, n0, 2));
    n1 = fmaxf(n1, __shfl_xor_sync(0xffffffffu, n1, 2));
  }
  n0 *= -SM_C;
  n1 *= -SM_C;
}
template <int J0, int J1>
__device__ __forceinline__ void softmax_exp(float (&sc)[64], uint32_t (&pf)[32], float n0, float n1, float& l0, float& l1) {
#pragma unroll
  for (int j = J0; j < J1; j++) {
    const float e0 = ex2(fmaf(sc[4 * j], SM_C, n0));
    const float e1 = ex2(fmaf(sc[4 * j + 1], SM_C, n0));
    const float e2 = ex2(fmaf(sc[4 * j + 2], SM_C, n1));
    const float e3 = ex2(fmaf(sc[4 * j + 3], SM_C, n1));
    l0 += e0 + e1;
    l1 += e2 + e3;
    pf[2 * j] = pack_bf16(e0, e1);
    pf[2 * j + 1] = pack_bf16(e2, e3);
  }
  asm volatile("" : "+f"(l0), "+f"(l1)::"memory");
#pragma unroll
  for (int j = 2 * J0; j < 2 * J1; j++) asm volatile("" : "+r"(pf[j])::"memory");
}
__device__ __forceinline__ void row_inv(float& l0, float& l1) {
  l0 += __shfl_xor_sync(0xffffffffu, l0, 1);
  l1 += __shfl_xor_sync(0xffffffffu, l1, 1);
  l0 += __shfl_xor_sync(0xffffffffu, l0, 2);
  l1 += __shfl_xor_sync(0xffffffffu, l1, 2);
  l0 = __fdividef(1.f, l0);
  l1 = __fdividef(1.f, l1);
}
__device__ __forceinline__ void cvt_frag(uint32_t (&f)[32], float (&a)[64]) {
#pragma unroll
  for (int i = 0; i < 32; i++) f[i] = pack_bf16(a[2 * i], a[2 * i + 1]);
}

struct Ctx {
  uint32_t sb16, bars, rel_base;
  int wg;
  int z;
};
template <int T>
__device__ __forceinline__ void blk_begin(const Ctx& c) {
  mbar_wait(c.bars + (FT + T) * 8);
  turn_wait(c.wg);
}
template <int T>
__device__ __forceinline__ void blk_release(const Ctx& c) {
  FINE(T, 4);
  if (T < 36) release(c.rel_base, ET + T, ((LOCAL_ONLY >> (T & 31)) & 1) && T < 32 ? 1 : 2);
}
template <int T>
__device__ __forceinline__ uint32_t tile_addr(const Ctx& c) {
  uint32_t a = c.sb16;
  asm volatile("" : "+r"(a));
  return a + tslot(T) * SLOT16;
}

__device__ __forceinline__ void stsm(uint32_t addr, uint32_t a, uint32_t b, uint32_t c, uint32_t d) {
  asm volatile("stmatrix.sync.aligned.m8n8.x4.shared.b16 [%0], {%1, %2, %3, %4};" ::"r"(addr), "r"(a), "r"(b), "r"(c), "r"(d) : "memory");
}
__device__ __forceinline__ uint32_t st_addr(uint32_t row, int sw, int e) { return row + (e >> 2) * 16384 + (((2 * (e & 3)) ^ sw) << 4); }
__device__ __forceinline__ void proxy_fence() { asm volatile("fence.proxy.async.shared::cta;" ::: "memory"); }
__device__ __forceinline__ void st_frag(uint32_t row, int sw, uint32_t (&f)[32]) {
#pragma unroll
  for (int e = 0; e < 8; e++) stsm(st_addr(row, sw, e), f[4 * e], f[4 * e + 1], f[4 * e + 2], f[4 * e + 3]);
}
template <int E0 = 0, int E1 = 8>
__device__ __forceinline__ void st_acc(uint32_t row, int sw, float (&a)[64]) {
#pragma unroll
  for (int e = E0; e < E1; e++)
    stsm(st_addr(row, sw, e), pack_bf16(a[8 * e], a[8 * e + 1]), pack_bf16(a[8 * e + 2], a[8 * e + 3]),
         pack_bf16(a[8 * e + 4], a[8 * e + 5]), pack_bf16(a[8 * e + 6], a[8 * e + 7]));
}
__device__ __forceinline__ void ld_acc(uint32_t row, int sw, float (&a)[64]) {
#pragma unroll
  for (int e = 0; e < 8; e++) {
    uint32_t r[4];
    asm volatile("ldmatrix.sync.aligned.m8n8.x4.shared.b16 {%0, %1, %2, %3}, [%4];"
                 : "=r"(r[0]), "=r"(r[1]), "=r"(r[2]), "=r"(r[3]) : "r"(st_addr(row, sw, e)) : "memory");
#pragma unroll
    for (int i = 0; i < 4; i++) {
      uint32_t lo;
      asm("mul.lo.u32 %0, %1, 65536;" : "=r"(lo) : "r"(r[i]));
      a[8 * e + 2 * i] = __uint_as_float(lo);
      a[8 * e + 2 * i + 1] = __uint_as_float(r[i] & 0xFFFF0000u);
    }
  }
}
template <int OFF>
__device__ __forceinline__ void st_acc64(uint32_t row, int sw, float (&a)[32], float (&b)[64]) {
#pragma unroll
  for (int e = 0; e < 4; e++) {
    float v[8];
#pragma unroll
    for (int i = 0; i < 8; i++) v[i] = a[8 * e + i] + b[OFF + 8 * e + i];
    stsm(st_addr(row, sw, e), pack_bf16(v[0], v[1]), pack_bf16(v[2], v[3]), pack_bf16(v[4], v[5]), pack_bf16(v[6], v[7]));
  }
}

template <int T, class Issue, class Shadow>
__device__ __forceinline__ void block(const Ctx& c, Issue issue, Shadow shadow) {
  blk_begin<T>(c);
  WG_FENCE();
  issue(tile_addr<T>(c));
  WG_COMMIT();
  if (T < 39 || c.wg == 0) turn_pass(c.wg);
  constexpr bool HAS_SHADOW = !(T == 8 || T == 13 || T == 15 || T == 24 || (T > 33 && T != 36));
  if (HAS_SHADOW) {
    SCHED_FENCE();
    shadow();
    SCHED_FENCE();
  }
  WG_WAIT(0);
}

template <int T0, int NF, class SShadow, class Fill, class After, class PvShadow>
__device__ __forceinline__ void head(const Ctx& c, uint32_t (&q)[32], float (&sc)[64], float& l0, float& l1, SShadow sshadow, Fill fill,
                                     After after, PvShadow pvshadow) {
  constexpr bool FRESH = (T0 == 8);
  float n0, n1;
  int m0, m1;
  l0 = 0.f;
  l1 = 0.f;
  fence_frag<32, 0>(q);
  if (!FRESH) fence_acc(sc);
  block<T0>(c, [&](uint32_t a) { issue_s(sc, q, a, FRESH ? 0 : c.z); }, sshadow);
  fence_acc(sc);
  fence_frag<32, 0>(q);
  blk_release<T0>(c);
  softmax_max(sc, m0, m1);
  constexpr int E1 = (NF == 2) ? SEG2A : SEG3A, E2 = (NF == 2) ? 16 : SEG3B;
  block<T0 + 1>(c, [&](uint32_t a) { fill(0, a); }, [&]() {
    softmax_max_finish(sc, m0, m1, n0, n1);
    softmax_exp<0, E1>(sc, q, n0, n1, l0, l1);
  });
  blk_release<T0 + 1>(c);
  after(0);
  block<T0 + 2>(c, [&](uint32_t a) { fill(1, a); }, [&]() { softmax_exp<E1, E2>(sc, q, n0, n1, l0, l1); });
  blk_release<T0 + 2>(c);
  after(1);
  if constexpr (NF == 3) {
    block<T0 + 3>(c, [&](uint32_t a) { fill(2, a); }, [&]() { softmax_exp<E2, 16>(sc, q, n0, n1, l0, l1); });
    blk_release<T0 + 3>(c);
    after(2);
  }
  fence_frag<32, 0>(q);
  fence_acc(sc);
  block<T0 + NF + 1>(c, [&](uint32_t a) { issue_nt(sc, q, a, c.z); }, [&]() {
    row_inv(l0, l1);
    asm volatile("" : "+f"(l0), "+f"(l1)::"memory");
    pvshadow();
  });
  fence_acc(sc);
  fence_frag<32, 0>(q);
  blk_release<T0 + NF + 1>(c);
}
__device__ __forceinline__ void o_frag(uint32_t (&f)[32], float (&a)[64], float l0, float l1) {
#pragma unroll
  for (int j = 0; j < 16; j++) {
    f[2 * j] = pack_bf16(a[4 * j] * l0, a[4 * j + 1] * l0);
    f[2 * j + 1] = pack_bf16(a[4 * j + 2] * l1, a[4 * j + 3] * l1);
  }
}

__global__ void __cluster_dims__(2, 1, 1) __launch_bounds__(384, 1) fused_attn_kernel(const __grid_constant__ Params p) {
  extern __shared__ uint8_t smem_raw[];
  const uint32_t sb = (smem_u32(smem_raw) + 1023) & ~1023u;
  const uint32_t bars = sb + NSLOT * SLOT;
  const int tid = threadIdx.x;
  const int warp = __shfl_sync(0xffffffffu, tid >> 5, 0);
  const int rank = blockIdx.x & 1;
  const int cid = blockIdx.x >> 1;
#define MAPV 2
  int grp, bp;
  if (cid < 4) { grp = 15; bp = cid; }
  else if (cid < 36) { grp = (cid - 4) & 7; bp = (cid - 4) >> 3; }
  else { grp = 8 + (cid - 36) % 7; bp = (cid - 36) / 7; }
  const int blk = grp >> 3, g = grp & 7, b = bp * 2 + rank;

  const bool lead = elect_one();
  if (lead) {
    if (warp == 8) {
      PROF(40);
#pragma unroll
      for (int i = 0; i < 3; i++) mbar_init(bars + (FT + i) * 8, 1);
#pragma unroll
      for (int i = 0; i < 8; i++) mbar_init(bars + (FX + i) * 8, 1);
      mbar_init(bars + FA * 8, 1);
    } else {
#pragma unroll 1
      for (int i = 3 + warp - (warp > 8); i < FA; i += 11) {
        uint32_t cnt = 1;
        if (i >= SF && i < SE) cnt = 4;
        if (i >= ET && i < SF) cnt = (i < ET + 32 && ((LOCAL_ONLY >> (i - ET)) & 1)) ? 8 : 16;
        if (i < FX || i >= ET) mbar_init(bars + i * 8, cnt);
      }
    }
    asm volatile("fence.mbarrier_init.release.cluster;" ::: "memory");
  }
  __syncwarp();
  asm volatile("barrier.cluster.arrive.relaxed.aligned;" ::: "memory");

  if (warp >= 8) {
    asm volatile("setmaxnreg.dec.sync.aligned.u32 40;");
    if (warp == 8) {
      const CUtensorMap* tw = &p.wq[blk];
      const CUtensorMap* tk = &p.k[blk];
      const CUtensorMap* tv = &p.v[blk];
      const CUtensorMap* tu = &p.wo[blk];
      if (lead) {
#define NNOMC 3
#define XAHEAD 0
        mbar_expect_tx(bars + FA * 8, 8192 + 16384);
        tma_2d(sb, &p.x[blk], 0, b * 128, bars + FA * 8);
        tma_3d(sb + 4 * SLOT, tw, 0, 0, g * 8, bars + FA * 8);
        mbar_expect_tx(bars + FT * 8, 16384);
        tma_3d(sb + 4 * SLOT + 16384, tw, 0, 32, g * 8, bars + FT * 8);
        mbar_expect_tx(bars + FX * 8, 8192);
        tma_2d(sb + 8192, &p.x[blk], 0, b * 128 + 64, bars + FX * 8);
#pragma unroll 1
        for (int s = 1; s < NNOMC; s++) {
          mbar_expect_tx(bars + (FX + s) * 8, 16384);
          tma_2d(sb + s * 16384, &p.x[blk], s * 64, b * 128, bars + (FX + s) * 8);
          mbar_expect_tx(bars + (FT + s) * 8, SLOT);
          tma_3d(sb + (4 + s) * SLOT, tw, 0, s * 64, g * 8, bars + (FT + s) * 8);
          tma_3d(sb + (4 + s) * SLOT + 16384, tw, 0, s * 64 + 32, g * 8, bars + (FT + s) * 8);
          tma_2d(sb + s * 16384 + 8192, &p.x[blk], s * 64, b * 128 + 64, bars + (FX + s) * 8);
        }
        PROF(54);
      }
      __syncwarp();
      asm volatile("barrier.cluster.wait.acquire.aligned;" ::: "memory");
      if (lead) {
        PROF(55);
        const int kvrow = (b * 32 + g * 4) * 128;
        int nkv = 0, nq = 0, nu = 0;
#pragma unroll 1
        for (int t = NNOMC; t < 40; t++) {
          const int type = (t < 8) ? 4 : (int)((types_8_39() >> (2 * (t - 8))) & 3);
          const uint32_t dst = sb + tslot(t) * SLOT;
          const uint32_t fb = bars + (FT + t) * 8;
          if (t >= 3) mbar_wait(bars + (ET + tpred(t)) * 8);
          mbar_expect_tx(fb, SLOT);
          if (type == 4) {
            tma_3d_mc(dst + rank * 16384, tw, 0, t * 64 + rank * 32, g * 8, fb);
            mbar_expect_tx(bars + (FX + t) * 8, 16384);
            tma_2d(sb + t * 16384, &p.x[blk], t * 64, b * 128, bars + (FX + t) * 8);
            tma_2d(sb + t * 16384 + 8192, &p.x[blk], t * 64, b * 128 + 64, bars + (FX + t) * 8);
          } else if (type < 2) {
            tma_3d(dst, type ? tv : tk, 0, kvrow + (nkv >> 1) * 128, 0, fb);
            nkv++;
          } else if (type == 2) {
            const int qi = (0x76534210 >> (4 * nq)) & 7;
            tma_2d_mc(dst + rank * 16384, &p.wq2[blk], g * 512 + 256 + (qi >> 2) * 128 + rank * 64, (qi & 3) * 128, fb);
            nq++;
          } else {
            const int ch = (nu < 14) ? (int)(ULIST >> (4 * nu)) & 0xF : 14 + rank;
            const int half = (nu < 14) ? rank : nu & 1;
            tma_2d_mc(dst + rank * 16384, tu, (((ch >> 2) + g) & 3) * 128 + half * 64, g * 512 + (ch & 3) * 128, fb);
            nu++;
          }
        }
        PROF(41);
      }
    } else if (warp == 11) {
      asm volatile("barrier.cluster.wait.acquire.aligned;" ::: "memory");
      const int lane = tid & 31;
#define ZT 24
      mbar_wait(bars + (FT + ZT) * 8);
      char* o = p.out_ptr + (size_t)(b * 128) * 2048 + blk * 1024 + g * 128;
#define ZSLEEP 20
#pragma unroll 1
      for (int i = 0; i < 32; i++) {
        const int e = i * 32 + lane;
        *reinterpret_cast<uint4*>(o + (size_t)(e >> 3) * 2048 + (e & 7) * 16) = make_uint4(0, 0, 0, 0);
        __nanosleep(ZSLEEP);
      }
      __syncwarp();
      if (lead) {
        unsigned int* cnt = &g_zero_cnt[(blk * 8 + b) * 32];
        unsigned int old;
        asm volatile("fence.acq_rel.gpu;" ::: "memory");
        asm volatile("atom.relaxed.gpu.global.add.u32 %0, [%1], 1;" : "=r"(old) : "l"(cnt) : "memory");
        const unsigned int target = (old & ~7u) + 8;
        unsigned int cur;
        int it = 0;
        do {
          asm volatile("ld.acquire.gpu.global.u32 %0, [%1];" : "=r"(cur) : "l"(cnt) : "memory");
          if (++it > (1 << 22)) __trap();
          if ((int)(cur - target) < 0) __nanosleep(200);
        } while ((int)(cur - target) < 0);
        asm volatile("fence.proxy.async;" ::: "memory");
        asm volatile("prefetch.tensormap [%0];" ::"l"(&p.out) : "memory");
#pragma unroll 1
        for (int i = 0; i < 16; i++) {
          const int w = i & 1, hf = (i >> 1) & 1;
          mbar_wait(bars + (SF + i) * 8);
          asm volatile("cp.reduce.async.bulk.tensor.2d.global.shared::cta.add.tile.bulk_group [%0, {%2, %3}], [%1];" ::"l"(&p.out),
                       "r"(sb + (i >= 12 ? 2 : 3) * SLOT + w * 8192 + hf * 16384),
                       "r"(blk * 512 + ((((0x3201 >> (4 * (i >> 2))) & 3) + g) & 3) * 128 + hf * 64), "r"(b * 128 + w * 64)
                       : "memory");
          asm volatile("cp.async.bulk.commit_group;" ::: "memory");
          if (i >= 1 && i < 9) {
            asm volatile("cp.async.bulk.wait_group.read 1;" ::: "memory");
            mbar_arrive(bars + (SE + i - 1) * 8);
          }
        }
        asm volatile("cp.async.bulk.wait_group.read 0;" ::: "memory");
      }
    } else {
      const int i = tid - 288;
      uint32_t acc = 0;
#define TDEPTH 3
#define TPACE 1100
#define TREL
      {
        const char* w = p.wq_ptr[blk] + g * 1024;
        asm volatile("barrier.cluster.wait.acquire.aligned;" ::: "memory");
        {
          uint32_t v[3];
#pragma unroll
          for (int n = 0; n < 2; n++) {
            const int q = i >> 4, r = i & 15;
            const int code = (0x776D5C43 >> (4 * (n * 4 + q))) & 0xF;
            const char* a;
            if (code < 8) a = w + (size_t)(code * 64 + b * 8 + (r >> 1)) * 8192 + (r & 1) * 256;
            else a = p.x_ptr[blk] + (size_t)(b * 128 + g * 16 + r) * 1024 + (code - 10) * 256;
#define TW0 0
#define TW1 2
            if ((n == 0 ? TW0 : TW1) >= 0) mbar_wait(bars + (FT + (n == 0 ? TW0 : TW1)) * 8);
            asm volatile("ld.global.cg.L2::256B.u32 %0, [%1];" : "=r"(v[n + 1]) : "l"(a) : "memory");
          }
          const char* kp = p.k_ptr[blk] + (size_t)(b * 32 + g * 4) * 32768 + i * 256;
          const char* vp = p.v_ptr[blk] + (size_t)(b * 32 + g * 4) * 32768 + i * 256;
          constexpr uint64_t RT = (2ull << 4) | (5ull << 6) | (2ull << 10) | (5ull << 16) | (3ull << 24) | (5ull << 26) | (3ull << 34) |
                                  (5ull << 36) | (15ull << 40);
          int nk = 0, nv = 0, nq = 0, nu = 0;
#define TOFF 600
          uint32_t tnext = (uint32_t)clock64() + TOFF + (warp - 9) * (TPACE / 2);
          uint32_t u[TDEPTH];
#pragma unroll
          for (int q = 0; q < TDEPTH; q++) u[q] = (q >= TDEPTH - 2) ? v[q - (TDEPTH - 2) + 1] : 0;
#pragma unroll 1
          for (int n0 = 0; n0 < 22; n0 += TDEPTH) {
#pragma unroll
            for (int q = 0; q < TDEPTH; q++) {
              const int n = n0 + q;
              const int type = (int)((RT >> (2 * n)) & 3);
              const char* a;
              if (type == 0) a = kp + (nk++) * 16384;
              else if (type == 1) a = vp + (nv++) * 16384;
              else if (type == 2) a = w + (size_t)(i * 8 + b) * 8192 + 512 + (nq++) * 256;
              else a = p.wo_ptr[blk] + (size_t)(g * 512 + i * 8 + b) * 1024 + (((nu++) + g) & 3) * 256;
              acc ^= u[q];
              asm volatile("" ::"r"(acc) : "memory");
              while ((int)((uint32_t)clock64() - tnext) < 0) __nanosleep(40);
              tnext = (uint32_t)clock64() + (acc & p.zero) + TPACE;
              if (n < 22) asm volatile("ld.global.cg.L2::256B.u32 %0, [%1];" : "=r"(u[q]) : "l"(a) : "memory");
              if (warp == 9 && (n & 3) == 3) PROFW(42 + (n >> 2));
            }
          }
#pragma unroll
          for (int q = 0; q < TDEPTH; q++) acc ^= u[q];
        }
      }
      if (acc == 0x9e3779b9u && p.zero) g_zero_cnt[1] = acc;
    }
  } else {
    asm volatile("setmaxnreg.inc.sync.aligned.u32 232;");
    const int wg = warp >> 2;
    const int lane = tid & 31;
    uint32_t rel_base;
    asm volatile("mapa.shared::cluster.u32 %0, %1, %2;" : "=r"(rel_base) : "r"(bars), "r"(rank ^ (lane & 1)));
    if (wg == 1) turn_pass(1);
    asm volatile("barrier.cluster.wait.acquire.aligned;" ::: "memory");
    PROF(wg * 20 + 0);
    const uint32_t sb16 = (sb & 0x3FFFF) >> 4;
    const Ctx c{sb16, bars, rel_base, wg, (int)p.zero};
    const uint32_t xw = sb16 + wg * 512;
    uint32_t c0[32], c1[32];
    {
      float acc[128];
      int slot = 4;
      mbar_wait(bars + FA * 8);
      if (wg == 1) mbar_wait(bars + FX * 8);
      turn_wait(wg);
      WG_FENCE();
      wgmma_ss_n256_tb1(acc, xw + DK, sb16 + 4 * SLOT16 + DW, 0);
      wgmma_ss_n256_tb1(acc, xw + DK + 2, sb16 + 4 * SLOT16 + DW + 128, 1);
      WG_COMMIT();
      mbar_wait(bars + FT * 8);
      WG_FENCE();
      wgmma_ss_n256_tb1(acc, xw + DK + 4, sb16 + 4 * SLOT16 + DW + 1024, 1);
      wgmma_ss_n256_tb1(acc, xw + DK + 6, sb16 + 4 * SLOT16 + DW + 1024 + 128, 1);
      WG_COMMIT();
      turn_pass(wg);
      WG_WAIT(0);
      fence_acc(acc);
      release(rel_base, ET, 2);
      slot = 5;
#pragma unroll 1
      for (int t = 1; t < 8; t++) {
        mbar_wait(bars + (FX + t) * 8);
        mbar_wait(bars + (FT + t) * 8);
        const uint32_t da = xw + t * 1024 + DK;
        const uint32_t db = sb16 + slot * SLOT16 + DW;
        turn_wait(wg);
        fence_acc(acc);
        WG_FENCE();
#pragma unroll
        for (int j = 0; j < 4; j++) wgmma_ss_n256_tb1(acc, da + j * 2, db + (j >> 1) * 1024 + (j & 1) * 128, 1);
        WG_COMMIT();
        turn_pass(wg);
        WG_WAIT(0);
        fence_acc(acc);
        FINE(t, 4);
        release(rel_base, ET + t, t == 5 ? 1 : 2);
        slot = (slot == 6) ? 4 : slot + 1;
      }
#pragma unroll
      for (int i = 0; i < 32; i++) {
        c0[i] = pack_bf16(acc[2 * i], acc[2 * i + 1]);
        c1[i] = pack_bf16(acc[64 + 2 * i], acc[64 + 2 * i + 1]);
      }
    }
    const int srow = (lane & 7) + ((lane >> 3) & 1) * 8;
    const uint32_t prow = sb + warp * 2048 + srow * 128;
    const int sw = (lane >> 4) ^ (lane & 7);
    auto nop = []() {};
    auto stage_lo = [&](float(&a)[64], int f) {
      if (f >= 1) mbar_wait(bars + (SE + 4 * (f - 1) + wg) * 8);
      st_acc<0, 4>(prow + 3 * SLOT, sw, a);
    };
    auto stage_hi = [&](float(&a)[64], int f) {
      if (f >= 1) mbar_wait(bars + (SE + 4 * (f - 1) + 2 + wg) * 8);
      st_acc<4, 8>(prow + 3 * SLOT, sw, a);
    };
    auto publish = [&](int f, int hf) {
      proxy_fence();
      __syncwarp();
      if (lead) mbar_arrive(bars + (SF + 4 * f + 2 * hf + wg) * 8);
    };
    float ba[64];
    float bb[64];
    float l0, l1;
    head<8, 3>(c, c0, ba, l0, l1, nop, [&](int i, uint32_t a) { issue_q(bb, xw + i * SLOT16, a, i != 0); }, [&](int) { fence_acc(bb); }, nop);
    o_frag(c0, ba, l0, l1);
    fence_frag<32, 0>(c0);
    fence_acc(ba);
    block<13>(c, [&](uint32_t a) { issue_q(ba, xw, a, c.z); }, nop);
    fence_acc(ba);
    blk_release<13>(c);
    block<14>(c, [&](uint32_t a) { issue_q(bb, xw + 3 * SLOT16, a, 1); }, [&]() {
      st_frag(prow, sw, c0);
    });
    fence_acc(bb);
    blk_release<14>(c);
    cvt_frag(c0, bb);
    head<15, 3>(c, c1, bb, l0, l1, nop, [&](int i, uint32_t a) { issue_q(ba, xw + (i + 1) * SLOT16, a, 1); },
                [&](int i) {
                  fence_acc(ba);
                  if (i == 0) proxy_fence();
                },
                nop);
    o_frag(c1, bb, l0, l1);
    fence_frag<32, 0>(c1);
    head<20, 2>(c, c0, bb, l0, l1,
                [&]() {
                  st_frag(prow + SLOT, sw, c1);
                  cvt_frag(c1, ba);
                  fence_frag<32, 0>(c1);
                  fence_acc(ba);
                },
                [&](int i, uint32_t a) { issue_q(ba, xw + i * SLOT16, a, i ? 1 : c.z); },
                [&](int i) {
                  fence_acc(ba);
                  if (i == 0) proxy_fence();
                },
                nop);
    o_frag(c0, bb, l0, l1);
    fence_frag<32, 0>(c0);
    block<24>(c, [&](uint32_t a) { issue_nt(ba, c0, a, 1); }, nop);
    fence_acc(ba);
    blk_release<24>(c);
    head<25, 3>(c, c1, bb, l0, l1,
                [&]() {
                  st_acc(prow + 3 * SLOT, sw, ba);
                  fence_acc(ba);
                },
                [&](int i, uint32_t a) {
                  if (i < 2) issue_q(ba, xw + i * SLOT16, a, i ? 1 : c.z);
                  else issue_nt(ba, c0, a, 1);
                },
                [&](int i) {
                  fence_acc(ba);
                  fence_frag<32, 0>(c0);
                },
                nop);
    o_frag(c1, bb, l0, l1);
    fence_frag<32, 0>(c1);
    block<30>(c, [&](uint32_t a) { issue_nt(ba, c1, a, 1); }, [&]() {
      __syncwarp();
      ld_acc(prow + 3 * SLOT, sw, bb);
      fence_acc(bb);
    });
    fence_acc(ba);
    blk_release<30>(c);
    stage_lo(ba, 0);
    publish(0, 0);
    block<31>(c, [&](uint32_t a) { issue_nt(bb, c1, a, 1); }, [&]() { stage_hi(ba, 0); });
    fence_acc(bb);
    fence_acc(ba);
    blk_release<31>(c);
    publish(0, 1);
    block<32>(c, [&](uint32_t a) { issue_q(ba, xw, a, c.z); }, [&]() { stage_lo(bb, 1); });
    blk_release<32>(c);
    publish(1, 0);
    block<33>(c, [&](uint32_t a) { issue_q(ba, xw + SLOT16, a, 1); }, [&]() { stage_hi(bb, 1); });
    blk_release<33>(c);
    publish(1, 1);
    block<34>(c, [&](uint32_t a) { issue_nt(ba, c0, a, 1); }, nop);
    blk_release<34>(c);
    block<35>(c, [&](uint32_t a) { issue_nt(ba, c1, a, 1); }, nop);
    fence_acc(ba);
    blk_release<35>(c);
    stage_lo(ba, 2);
    publish(2, 0);
    fence_acc(bb);
    block<36>(c, [&](uint32_t a) { issue_q(bb, xw, a, c.z); }, [&]() { stage_hi(ba, 2); });
    blk_release<36>(c);
    publish(2, 1);
    block<37>(c, [&](uint32_t a) { issue_q(bb, xw + SLOT16, a, 1); }, nop);
    fence_acc(bb);
    blk_release<37>(c);
    float dl[32], dh[32];
    block<38>(c, [&](uint32_t a) { issue_nt64(dl, c0, c1, a); }, nop);
    fence_acc(dl);
    blk_release<38>(c);
    st_acc64<0>(prow + 2 * SLOT, sw, dl, bb);
    publish(3, 0);
    block<39>(c, [&](uint32_t a) { issue_nt64(dh, c0, c1, a); }, nop);
    fence_acc(dh);
    blk_release<39>(c);
    st_acc64<32>(prow + 2 * SLOT + 16384, sw, dh, bb);
    publish(3, 1);
  }
}

typedef CUresult (*EncodeFn)(CUtensorMap*, CUtensorMapDataType, cuuint32_t, void*, const cuuint64_t*, const cuuint64_t*,
                             const cuuint32_t*, const cuuint32_t*, CUtensorMapInterleave, CUtensorMapSwizzle,
                             CUtensorMapL2promotion, CUtensorMapFloatOOBfill);

void encode(EncodeFn fn, CUtensorMap* m, const void* ptr, int rank, const cuuint64_t* dims, const cuuint64_t* strides,
            const cuuint32_t* box) {
  cuuint32_t es[3] = {1, 1, 1};
  fn(m, CU_TENSOR_MAP_DATA_TYPE_BFLOAT16, rank, const_cast<void*>(ptr), dims, strides, box, es, CU_TENSOR_MAP_INTERLEAVE_NONE,
     CU_TENSOR_MAP_SWIZZLE_128B, CU_TENSOR_MAP_L2_PROMOTION_L2_256B, CU_TENSOR_MAP_FLOAT_OOB_FILL_NONE);
}

}

extern "C" void kernel_launch(void* const* d_in, const int* in_sizes, int n_in, void* d_out, int out_size) {
  (void)in_sizes; (void)n_in; (void)out_size;
  static EncodeFn fn = nullptr;
  if (!fn) {
    void* f = nullptr;
    cudaDriverEntryPointQueryResult qr;
    cudaGetDriverEntryPoint("cuTensorMapEncodeTiled", &f, cudaEnableDefault, &qr);
    fn = (EncodeFn)f;
    cudaFuncSetAttribute(fused_attn_kernel, cudaFuncAttributeMaxDynamicSharedMemorySize, SMEM_BYTES);
  }
  Params p;
  for (int i = 0; i < 2; i++) {
    const void* x = d_in[i * 5 + 0];
    const void* k = d_in[i * 5 + 1];
    const void* v = d_in[i * 5 + 2];
    const void* wq = d_in[i * 5 + 3];
    const void* wo = d_in[i * 5 + 4];
    {
      cuuint64_t d[2] = {512, 1024}, s[1] = {1024};
      cuuint32_t bx[2] = {64, 64};
      encode(fn, &p.x[i], x, 2, d, s, bx);
    }
    {
      cuuint64_t d[3] = {64, 512, 64}, s[2] = {8192, 128};
      cuuint32_t bx[3] = {64, 32, 4};
      encode(fn, &p.wq[i], wq, 3, d, s, bx);
    }
    {
      cuuint64_t d[2] = {4096, 512}, s[1] = {8192};
      cuuint32_t bx[2] = {64, 128};
      encode(fn, &p.wq2[i], wq, 2, d, s, bx);
    }
    {
      cuuint64_t d[3] = {64, 32768, 2}, s[2] = {256, 128};
      cuuint32_t bx[3] = {64, 128, 2};
      encode(fn, &p.k[i], k, 3, d, s, bx);
      encode(fn, &p.v[i], v, 3, d, s, bx);
    }
    {
      cuuint64_t d[2] = {512, 4096}, s[1] = {1024};
      cuuint32_t bx[2] = {64, 128};
      encode(fn, &p.wo[i], wo, 2, d, s, bx);
    }
    p.x_ptr[i] = (const char*)x;
    p.wq_ptr[i] = (const char*)wq;
    p.k_ptr[i] = (const char*)k;
    p.v_ptr[i] = (const char*)v;
    p.wo_ptr[i] = (const char*)wo;
  }
  {
    cuuint64_t d[2] = {1024, 1024}, s[1] = {2048};
    cuuint32_t bx[2] = {64, 64};
    encode(fn, &p.out, d_out, 2, d, s, bx);
  }
  p.out_ptr = (char*)d_out;
  p.zero = 0;
  fused_attn_kernel<<<128, 384, SMEM_BYTES, cudaStreamPerThread>>>(p);
}
```
